```python
import torch

def _softmax(x, axis=-1):
    return torch.softmax(x, dim=axis)

def _gelu(x):
    return torch.nn.functional.gelu(x, approximate='tanh')

def _silu(x):
    return torch.nn.functional.silu(x)

def _sigmoid(x):
    return torch.sigmoid(x)

def _layernorm(x, axis=-1, eps=1e-05):
    m = x.mean(dim=axis, keepdim=True)
    v = x.var(dim=axis, keepdim=True, unbiased=False)
    return (x - m) / torch.sqrt(v + eps)

def _scatter_add(tgt, idx, src, axis=0):
    return tgt.clone().index_add_(axis, idx, src)

def _segment_sum(src, seg, n):
    out = torch.zeros((n,) + src.shape[1:], dtype=src.dtype)
    return out.index_add_(0, seg, src)

def _pad(x, pw):
    flat = tuple((v for pair in reversed(pw) for v in pair))
    return torch.nn.functional.pad(x, flat)
kernel_name = 'adaLN_cond__memory_aug_recurrent_mem_tr__moe_arch_mod__prompt'

def setup_inputs():

    _w = lambda a: (lambda t: t.to(torch.bfloat16) if t.is_floating_point() else t)(torch.as_tensor(a))

    def _A_setup():
        B, S, Dm = (1, 2048, 640)
        H, Dh = (32, 192)
        M, seg = (8, 32)
        seg = min(seg, S)
        S = S // seg * seg
        return {'x': _w((lambda *s: torch.randn(*s, dtype=torch.bfloat16) * 0.05)(B, S, Dm)), 'mem0': _w((lambda *s: torch.randn(*s, dtype=torch.bfloat16) * 0.4)(B, M, Dm)), 'Wq': _w((lambda *s: torch.randn(*s, dtype=torch.bfloat16) * 3.2)(Dm, H, Dh) * Dm ** (-0.5)), 'Wk': _w((lambda *s: torch.randn(*s, dtype=torch.bfloat16) * 3.2)(Dm, H, Dh) * Dm ** (-0.5)), 'Wv': _w((lambda *s: torch.randn(*s, dtype=torch.bfloat16) * 0.4)(Dm, H, Dh) * Dm ** (-0.5)), 'Wo': _w((lambda *s: torch.randn(*s, dtype=torch.bfloat16) * 0.4)(H, Dh, Dm) * (H * Dh) ** (-0.5)), 'seg_len': seg}
    _A_in = _A_setup()

    def _B_setup():
        B, S, D, F, C = (1, 2048, 640, 1536, 8)
        return {'x': _w((lambda *s: torch.randn(*s, dtype=torch.bfloat16) * 0.05)(B, S, D)), 'w_r': _w((lambda *s: torch.randn(*s, dtype=torch.bfloat16) * 0.05)(D)), 'w_gate': _w((lambda *s: torch.randn(*s, dtype=torch.bfloat16) * 0.05)(D, F)), 'w_up': _w((lambda *s: torch.randn(*s, dtype=torch.bfloat16) * 0.05)(D, F)), 'w_down': _w((lambda *s: torch.randn(*s, dtype=torch.bfloat16) * 0.05)(F, D))}
    _B_in = _B_setup()
    return {'A_x': _A_in['x'], 'A_mem0': _A_in['mem0'], 'A_Wq': _A_in['Wq'], 'A_Wk': _A_in['Wk'], 'A_Wv': _A_in['Wv'], 'A_Wo': _A_in['Wo'], 'A_seg_len': _A_in['seg_len'], 'B_x': _B_in['x'], 'B_w_r': _B_in['w_r'], 'B_w_gate': _B_in['w_gate'], 'B_w_up': _B_in['w_up'], 'B_w_down': _B_in['w_down'], 'c': _w((lambda *s: torch.randn(*s, dtype=torch.bfloat16) * 0.05)(1, 640) * 8.0), 'w_mod': _w((lambda *s: torch.randn(*s, dtype=torch.bfloat16) * 0.05)(640, 6 * 640) * 640 ** (-0.5) * 8.0)}

def reference(A_x, A_mem0, A_Wq, A_Wk, A_Wv, A_Wo, A_seg_len, B_x, B_w_r, B_w_gate, B_w_up, B_w_down, c, w_mod):

    def _A_ref(x, mem0, Wq, Wk, Wv, Wo, seg_len):
        B, S, Dm = x.shape
        H, Dh = (Wq.shape[1], Wq.shape[2])
        M = mem0.shape[1]
        scale = Dh ** (-0.5)
        n_seg = S // seg_len
        L = M + seg_len
        idx = torch.arange(L)
        mask = (idx[:, None] < M) | (idx[:, None] >= idx[None, :])
        mem = mem0
        outs = []
        for s in range(n_seg):
            xs = x[:, s * seg_len:(s + 1) * seg_len, :].clone()
            h = torch.concatenate([mem, xs], axis=1)
            q = torch.einsum('btd,dhe->bhte', h, Wq)
            k = torch.einsum('btd,dhe->bhte', h, Wk)
            v = torch.einsum('btd,dhe->bhte', h, Wv)
            scores = torch.einsum('bhqe,bhke->bhqk', q, k) * scale
            scores = torch.where(mask[None, None], scores, -1000000000.0)
            p = _softmax(scores, axis=-1)
            o = torch.einsum('bhqk,bhke->bhqe', p, v)
            o = torch.einsum('bhte,hed->btd', o, Wo)
            mem = o[:, :M, :].clone()
            outs.append(o[:, M:, :])
        return torch.concatenate(outs, axis=1)

    def _B_ref(x, w_r, w_gate, w_up, w_down):
        B, S, D = x.shape
        C = 8
        r = x @ w_r
        idx = torch.argsort(-r, axis=-1)[:, :C]
        idx_e = (lambda x, n, axis: torch.repeat_interleave(x, n, dim=axis))(idx.reshape(B, C, 1), D, axis=2)
        x_sel = (lambda x, i, axis: torch.take_along_dim(x, i, dim=axis))(x, idx_e, axis=1)
        g = _silu(x_sel @ w_gate)
        u = x_sel @ w_up
        y = g * u @ w_down
        r_sel = _sigmoid((lambda x, i, axis: torch.take_along_dim(x, i, dim=axis))(r, idx, axis=1))
        y = y * r_sel.reshape(B, C, 1)
        b_off = (torch.arange(B) * S).reshape(B, 1)
        flat_idx = (idx + b_off).reshape(B * C)
        zero = (x * 0.0).reshape(B * S, D)
        upd = _scatter_add(zero, flat_idx, y.reshape(B * C, D), axis=0)
        return x + upd.reshape(B, S, D)
    x = A_x
    mod = (_silu(c) @ w_mod).reshape(c.shape[0], 6, 1, -1)
    sa, ca, ga, sb, cb, gb = (mod[:, 0].clone(), mod[:, 1].clone(), mod[:, 2].clone(), mod[:, 3].clone(), mod[:, 4].clone(), mod[:, 5].clone())
    h = _layernorm(x, axis=-1) * (1 + ca) + sa
    x = x + ga * _A_ref(h, A_mem0, A_Wq, A_Wk, A_Wv, A_Wo, A_seg_len)
    h = _layernorm(x, axis=-1) * (1 + cb) + sb
    x = x + gb * _B_ref(h, B_w_r, B_w_gate, B_w_up, B_w_down)
    return x
```

```cpp
#include <cuda_runtime.h>
#include <cuda_bf16.h>
#include <cuda.h>
#include <stdint.h>
#include <stdio.h>
#include <string.h>
#include <stdlib.h>

typedef __nv_bfloat16 bf16;
constexpr int S_TOK = 2048, DM = 640, NH = 32, DH = 192, HD = NH * DH, NSEG = 64, SEG = 32, FF = 1536;

__device__ bf16 g_mod[6 * DM];
__device__ bf16 g_h[S_TOK * DM];
__device__ bf16 g_q[S_TOK * HD];
__device__ bf16 g_k[S_TOK * HD];
__device__ bf16 g_v[S_TOK * HD];
__device__ bf16 g_o[S_TOK * HD];
__device__ bf16 g_km[NSEG * NH * 8 * DH];
__device__ bf16 g_vm[NSEG * NH * 8 * DH];
__device__ bf16 g_A[S_TOK * DM];
__device__ bf16 g_x1[S_TOK * DM];
__device__ bf16 g_h2[S_TOK * DM];
__device__ bf16 g_r[S_TOK];
__device__ int g_idx[8];
__device__ __align__(128) uint32_t g_gu[FF / 8 * 32];
__device__ __align__(128) uint32_t g_memg[NSEG * 2560];
__device__ __align__(128) uint32_t g_part[80 * 32 * 32];
__device__ uint32_t g_stamp[NSEG * 96];
#define B_FINE 8
constexpr int KSPLIT = 16, SLABS = 3;
__device__ bf16 g_slab[SLABS * KSPLIT * 128 * DM];
struct __align__(128) BlockFlags {
    uint32_t qk, vb, c1, pad0;
    uint32_t at, c2, pad1[2];
    uint32_t o, c3, pad2[2];
    uint32_t ln, c0, pad3[18];
};
struct __align__(128) Flags {
    BlockFlags b[16];
    uint32_t v[16 * 32];
    uint32_t seg[64 * 32];
    uint32_t pair[16 * 16];
    uint32_t mod, h, pad1[30], gu, pad2[31], done, pad3[31];
};
__device__ Flags g_flags;

__device__ __forceinline__ uint32_t smem_u32(const void* p) { return (uint32_t)__cvta_generic_to_shared(p); }
__device__ __forceinline__ uint32_t pack2(float lo, float hi) {
    uint32_t r; asm("cvt.rn.bf16x2.f32 %0, %1, %2;" : "=r"(r) : "f"(hi), "f"(lo)); return r;
}
__device__ __forceinline__ float bfr(float x) { return __uint_as_float(pack2(0.f, x)); }
__device__ __forceinline__ float inv_std(float var) {
    float s, r; asm("sqrt.approx.f32 %0, %1;" : "=f"(s) : "f"(bfr(bfr(var) + 1e-5f))); asm("rcp.approx.f32 %0, %1;" : "=f"(r) : "f"(bfr(s))); return r;
}
__device__ __forceinline__ float lo_f(uint32_t v) { return __uint_as_float(v << 16); }
__device__ __forceinline__ float hi_f(uint32_t v) { return __uint_as_float(v & 0xffff0000u); }
__device__ __forceinline__ void mbar_init(uint32_t bar, int cnt) { asm volatile("mbarrier.init.shared::cta.b64 [%0], %1;" :: "r"(bar), "r"(cnt) : "memory"); }
__device__ __forceinline__ void mbar_expect(uint32_t bar, int bytes) { asm volatile("mbarrier.arrive.expect_tx.shared::cta.b64 _, [%0], %1;" :: "r"(bar), "r"(bytes) : "memory"); }
__device__ __forceinline__ void mbar_arrive(uint32_t bar) { asm volatile("mbarrier.arrive.shared::cta.b64 _, [%0];" :: "r"(bar) : "memory"); }
__device__ __forceinline__ bool mbar_try(uint32_t bar, int par) {
    uint32_t ok; asm volatile("{ .reg .pred p; mbarrier.try_wait.parity.shared::cta.b64 p, [%1], %2; selp.u32 %0, 1, 0, p; }" : "=r"(ok) : "r"(bar), "r"(par) : "memory"); return ok;
}
__device__ __forceinline__ bool mbar_try_cluster(uint32_t bar, int par) {
    uint32_t ok; asm volatile("{ .reg .pred p; mbarrier.try_wait.parity.acquire.cluster.shared::cta.b64 p, [%1], %2; selp.u32 %0, 1, 0, p; }" : "=r"(ok) : "r"(bar), "r"(par) : "memory"); return ok;
}
__device__ __forceinline__ bool mbar_test(uint32_t bar, uint32_t par) {
    uint32_t ok; asm volatile("{ .reg .pred p; mbarrier.test_wait.parity.shared::cta.b64 p, [%1], %2; selp.u32 %0, 1, 0, p; }" : "=r"(ok) : "r"(bar), "r"(par) : "memory"); return ok;
}
constexpr int SPIN_LIMIT = 1 << 18;
__device__ __forceinline__ void mbar_wait(uint32_t bar, uint32_t par) {
    asm volatile("{ .reg .pred p, q; .reg .u32 n; mov.u32 n, 0;\n"
                 "W_%=: mbarrier.try_wait.parity.shared::cta.b64 p, [%0], %1;\n"
                 "@p bra.uni D_%=;\n"
                 "add.u32 n, n, 1; setp.lt.u32 q, n, 0x200000; @q bra.uni W_%=;\n"
                 "trap;\n"
                 "D_%=: }" :: "r"(bar), "r"(par) : "memory");
}
__device__ __forceinline__ void tma2d(uint32_t dst, const CUtensorMap* m, int c0, int c1, uint32_t bar) {
    asm volatile("cp.async.bulk.tensor.2d.shared::cluster.global.mbarrier::complete_tx::bytes [%0], [%1, {%3, %4}], [%2];"
        :: "r"(dst), "l"((uint64_t)m), "r"(bar), "r"(c0), "r"(c1) : "memory");
}
__device__ __forceinline__ void tma2d_mc(uint32_t dst, const CUtensorMap* m, int c0, int c1, uint32_t bar, uint16_t mask) {
    asm volatile("cp.async.bulk.tensor.2d.shared::cluster.global.mbarrier::complete_tx::bytes.multicast::cluster [%0], [%1, {%3, %4}], [%2], %5;"
        :: "r"(dst), "l"((uint64_t)m), "r"(bar), "r"(c0), "r"(c1), "h"(mask) : "memory");
}
__device__ __forceinline__ uint64_t policy_stream() { uint64_t p; asm("createpolicy.fractional.L2::evict_first.b64 %0, 1.0;" : "=l"(p)); return p; }
__device__ __forceinline__ void tma2d_ef(uint32_t dst, const CUtensorMap* m, int c0, int c1, uint32_t bar, uint64_t pol) {
    asm volatile("cp.async.bulk.tensor.2d.shared::cluster.global.mbarrier::complete_tx::bytes.L2::cache_hint [%0], [%1, {%3, %4}], [%2], %5;"
        :: "r"(dst), "l"((uint64_t)m), "r"(bar), "r"(c0), "r"(c1), "l"(pol) : "memory");
}
__device__ __forceinline__ void tma3d(uint32_t dst, const CUtensorMap* m, int row, int chunk, uint32_t bar) {
    asm volatile("cp.async.bulk.tensor.3d.shared::cluster.global.mbarrier::complete_tx::bytes [%0], [%1, {0, %3, %4}], [%2];"
        :: "r"(dst), "l"((uint64_t)m), "r"(bar), "r"(row), "r"(chunk) : "memory");
}
__device__ __forceinline__ void tma3d_ef(uint32_t dst, const CUtensorMap* m, int row, int chunk, uint32_t bar, uint64_t pol) {
    asm volatile("cp.async.bulk.tensor.3d.shared::cluster.global.mbarrier::complete_tx::bytes.L2::cache_hint [%0], [%1, {0, %3, %4}], [%2], %5;"
        :: "r"(dst), "l"((uint64_t)m), "r"(bar), "r"(row), "r"(chunk), "l"(pol) : "memory");
}
__device__ __forceinline__ void tma3d_store(const CUtensorMap* m, int row, int chunk, uint32_t src, uint64_t pol, bool hint) {
    if (hint) asm volatile("cp.async.bulk.tensor.3d.global.shared::cta.bulk_group.L2::cache_hint [%0, {0, %2, %3}], [%1], %4;"
        :: "l"((uint64_t)m), "r"(src), "r"(row), "r"(chunk), "l"(pol) : "memory");
    else asm volatile("cp.async.bulk.tensor.3d.global.shared::cta.bulk_group [%0, {0, %2, %3}], [%1];"
        :: "l"((uint64_t)m), "r"(src), "r"(row), "r"(chunk) : "memory");
}
__device__ __forceinline__ bool elect() { uint32_t p; asm volatile("{ .reg .pred e; elect.sync _|e, -1; selp.u32 %0, 1, 0, e; }" : "=r"(p)); return p; }
__device__ __forceinline__ uint2 ld_ef(const void* p, uint64_t pol) {
    uint2 v; asm volatile("ld.relaxed.gpu.global.L2::cache_hint.v2.u32 {%0,%1}, [%2], %3;" : "=r"(v.x), "=r"(v.y) : "l"(p), "l"(pol)); return v;
}
__device__ __forceinline__ void st_ef(void* p, uint2 v, uint64_t pol) {
    asm volatile("st.global.L2::cache_hint.v2.u32 [%0], {%1,%2}, %3;" :: "l"(p), "r"(v.x), "r"(v.y), "l"(pol) : "memory");
}
__device__ __forceinline__ void tma2d_prefetch(const CUtensorMap* m, int c0, int c1) {
    asm volatile("cp.async.bulk.prefetch.tensor.2d.L2.global [%0, {%1, %2}];" :: "l"((uint64_t)m), "r"(c0), "r"(c1) : "memory");
}
__device__ __forceinline__ void mbar_arrive_remote(uint32_t bar) { asm volatile("mbarrier.arrive.relaxed.cluster.shared::cluster.b64 _, [%0];" :: "r"(bar) : "memory"); }
__device__ __forceinline__ void tma2d_store(const CUtensorMap* m, int c0, int c1, uint32_t src) {
    asm volatile("cp.async.bulk.tensor.2d.global.shared::cta.bulk_group [%0, {%2, %3}], [%1];"
        :: "l"((uint64_t)m), "r"(src), "r"(c0), "r"(c1) : "memory");
}
__device__ __forceinline__ void bulk_g2s(uint32_t dst, const void* src, int bytes, uint32_t bar) {
    asm volatile("cp.async.bulk.shared::cluster.global.mbarrier::complete_tx::bytes [%0], [%1], %2, [%3];" :: "r"(dst), "l"(src), "r"(bytes), "r"(bar) : "memory");
}
__device__ __forceinline__ void ldsm4(uint32_t (&r)[4], uint32_t a) {
    asm volatile("ldmatrix.sync.aligned.m8n8.x4.shared.b16 {%0,%1,%2,%3}, [%4];" : "=r"(r[0]), "=r"(r[1]), "=r"(r[2]), "=r"(r[3]) : "r"(a) : "memory");
}
__device__ __forceinline__ void ldsm4t(uint32_t (&r)[4], uint32_t a) {
    asm volatile("ldmatrix.sync.aligned.m8n8.x4.trans.shared.b16 {%0,%1,%2,%3}, [%4];" : "=r"(r[0]), "=r"(r[1]), "=r"(r[2]), "=r"(r[3]) : "r"(a) : "memory");
}
__device__ __forceinline__ void stsm4(uint32_t a, uint32_t r0, uint32_t r1, uint32_t r2, uint32_t r3) {
    asm volatile("stmatrix.sync.aligned.m8n8.x4.shared.b16 [%0], {%1,%2,%3,%4};" :: "r"(a), "r"(r0), "r"(r1), "r"(r2), "r"(r3) : "memory");
}
__device__ __forceinline__ void stsm4t(uint32_t a, uint32_t r0, uint32_t r1, uint32_t r2, uint32_t r3) {
    asm volatile("stmatrix.sync.aligned.m8n8.x4.trans.shared.b16 [%0], {%1,%2,%3,%4};" :: "r"(a), "r"(r0), "r"(r1), "r"(r2), "r"(r3) : "memory");
}
__device__ __forceinline__ void stsm2t(uint32_t a, uint32_t r0, uint32_t r1) {
    asm volatile("stmatrix.sync.aligned.m8n8.x2.trans.shared.b16 [%0], {%1,%2};" :: "r"(a), "r"(r0), "r"(r1) : "memory");
}
__device__ __forceinline__ uint32_t movm_t(uint32_t v) { uint32_t r; asm volatile("movmatrix.sync.aligned.m8n8.trans.b16 %0, %1;" : "=r"(r) : "r"(v)); return r; }
__device__ __forceinline__ void mma16(float (&d)[4], uint32_t a0, uint32_t a1, uint32_t a2, uint32_t a3, uint32_t b0, uint32_t b1) {
    asm volatile("mma.sync.aligned.m16n8k16.row.col.f32.bf16.bf16.f32 {%0,%1,%2,%3}, {%4,%5,%6,%7}, {%8,%9}, {%0,%1,%2,%3};"
        : "+f"(d[0]), "+f"(d[1]), "+f"(d[2]), "+f"(d[3]) : "r"(a0), "r"(a1), "r"(a2), "r"(a3), "r"(b0), "r"(b1));
}
__device__ __forceinline__ void mma8(float (&d)[4], uint32_t a0, uint32_t a1, uint32_t b0) {
    asm volatile("mma.sync.aligned.m16n8k8.row.col.f32.bf16.bf16.f32 {%0,%1,%2,%3}, {%4,%5}, {%6}, {%0,%1,%2,%3};"
        : "+f"(d[0]), "+f"(d[1]), "+f"(d[2]), "+f"(d[3]) : "r"(a0), "r"(a1), "r"(b0));
}
__device__ __forceinline__ uint32_t mapa(uint32_t a, uint32_t r) { uint32_t o; asm volatile("mapa.shared::cluster.u32 %0, %1, %2;" : "=r"(o) : "r"(a), "r"(r)); return o; }
__device__ __forceinline__ void bar_sync(int id, int n) { asm volatile("bar.sync %0, %1;" :: "r"(id), "r"(n) : "memory"); }
__device__ __forceinline__ void bar_arrive(int id, int n) { asm volatile("bar.arrive %0, %1;" :: "r"(id), "r"(n) : "memory"); }
__device__ __forceinline__ uint64_t mkdesc(uint32_t addr, uint32_t lbo, uint32_t sbo) {
    return (uint64_t)((addr & 0x3FFFF) >> 4) | ((uint64_t)(lbo >> 4) << 16) | ((uint64_t)(sbo >> 4) << 32) | (1ull << 62);
}
#define WG_FENCE()  asm volatile("wgmma.fence.sync.aligned;" ::: "memory")
#define WG_COMMIT() asm volatile("wgmma.commit_group.sync.aligned;" ::: "memory")
#define WG_WAIT(n)  asm volatile("wgmma.wait_group.sync.aligned %0;" :: "n"(n) : "memory")

__device__ __forceinline__ void wgmma_ss_n192_tb(float (&d)[96], uint64_t a, uint64_t b, int acc) {
    asm volatile("{ .reg .pred p; setp.ne.b32 p, %98, 0;\n"
        "wgmma.mma_async.sync.aligned.m64n192k16.f32.bf16.bf16 {%0,%1,%2,%3,%4,%5,%6,%7,%8,%9,%10,%11,%12,%13,%14,%15,%16,%17,%18,%19,%20,%21,%22,%23,%24,%25,%26,%27,%28,%29,%30,%31,%32,%33,%34,%35,%36,%37,%38,%39,%40,%41,%42,%43,%44,%45,%46,%47,%48,%49,%50,%51,%52,%53,%54,%55,%56,%57,%58,%59,%60,%61,%62,%63,%64,%65,%66,%67,%68,%69,%70,%71,%72,%73,%74,%75,%76,%77,%78,%79,%80,%81,%82,%83,%84,%85,%86,%87,%88,%89,%90,%91,%92,%93,%94,%95}, %96, %97, p, 1, 1, 0, 1; }"
        : "+f"(d[0]), "+f"(d[1]), "+f"(d[2]), "+f"(d[3]), "+f"(d[4]), "+f"(d[5]), "+f"(d[6]), "+f"(d[7]), "+f"(d[8]), "+f"(d[9]), "+f"(d[10]), "+f"(d[11]), "+f"(d[12]), "+f"(d[13]), "+f"(d[14]), "+f"(d[15]), "+f"(d[16]), "+f"(d[17]), "+f"(d[18]), "+f"(d[19]), "+f"(d[20]), "+f"(d[21]), "+f"(d[22]), "+f"(d[23]), "+f"(d[24]), "+f"(d[25]), "+f"(d[26]), "+f"(d[27]), "+f"(d[28]), "+f"(d[29]), "+f"(d[30]), "+f"(d[31]), "+f"(d[32]), "+f"(d[33]), "+f"(d[34]), "+f"(d[35]), "+f"(d[36]), "+f"(d[37]), "+f"(d[38]), "+f"(d[39]), "+f"(d[40]), "+f"(d[41]), "+f"(d[42]), "+f"(d[43]), "+f"(d[44]), "+f"(d[45]), "+f"(d[46]), "+f"(d[47]), "+f"(d[48]), "+f"(d[49]), "+f"(d[50]), "+f"(d[51]), "+f"(d[52]), "+f"(d[53]), "+f"(d[54]), "+f"(d[55]), "+f"(d[56]), "+f"(d[57]), "+f"(d[58]), "+f"(d[59]), "+f"(d[60]), "+f"(d[61]), "+f"(d[62]), "+f"(d[63]), "+f"(d[64]), "+f"(d[65]), "+f"(d[66]), "+f"(d[67]), "+f"(d[68]), "+f"(d[69]), "+f"(d[70]), "+f"(d[71]), "+f"(d[72]), "+f"(d[73]), "+f"(d[74]), "+f"(d[75]), "+f"(d[76]), "+f"(d[77]), "+f"(d[78]), "+f"(d[79]), "+f"(d[80]), "+f"(d[81]), "+f"(d[82]), "+f"(d[83]), "+f"(d[84]), "+f"(d[85]), "+f"(d[86]), "+f"(d[87]), "+f"(d[88]), "+f"(d[89]), "+f"(d[90]), "+f"(d[91]), "+f"(d[92]), "+f"(d[93]), "+f"(d[94]), "+f"(d[95])
        : "l"(a), "l"(b), "r"(acc));
}

__device__ __forceinline__ void wgmma_ss_n128_tb(float (&d)[64], uint64_t a, uint64_t b, int acc) {
    asm volatile("{ .reg .pred p; setp.ne.b32 p, %66, 0;\n"
        "wgmma.mma_async.sync.aligned.m64n128k16.f32.bf16.bf16 {%0,%1,%2,%3,%4,%5,%6,%7,%8,%9,%10,%11,%12,%13,%14,%15,%16,%17,%18,%19,%20,%21,%22,%23,%24,%25,%26,%27,%28,%29,%30,%31,%32,%33,%34,%35,%36,%37,%38,%39,%40,%41,%42,%43,%44,%45,%46,%47,%48,%49,%50,%51,%52,%53,%54,%55,%56,%57,%58,%59,%60,%61,%62,%63}, %64, %65, p, 1, 1, 0, 1; }"
        : "+f"(d[0]), "+f"(d[1]), "+f"(d[2]), "+f"(d[3]), "+f"(d[4]), "+f"(d[5]), "+f"(d[6]), "+f"(d[7]), "+f"(d[8]), "+f"(d[9]), "+f"(d[10]), "+f"(d[11]), "+f"(d[12]), "+f"(d[13]), "+f"(d[14]), "+f"(d[15]), "+f"(d[16]), "+f"(d[17]), "+f"(d[18]), "+f"(d[19]), "+f"(d[20]), "+f"(d[21]), "+f"(d[22]), "+f"(d[23]), "+f"(d[24]), "+f"(d[25]), "+f"(d[26]), "+f"(d[27]), "+f"(d[28]), "+f"(d[29]), "+f"(d[30]), "+f"(d[31]), "+f"(d[32]), "+f"(d[33]), "+f"(d[34]), "+f"(d[35]), "+f"(d[36]), "+f"(d[37]), "+f"(d[38]), "+f"(d[39]), "+f"(d[40]), "+f"(d[41]), "+f"(d[42]), "+f"(d[43]), "+f"(d[44]), "+f"(d[45]), "+f"(d[46]), "+f"(d[47]), "+f"(d[48]), "+f"(d[49]), "+f"(d[50]), "+f"(d[51]), "+f"(d[52]), "+f"(d[53]), "+f"(d[54]), "+f"(d[55]), "+f"(d[56]), "+f"(d[57]), "+f"(d[58]), "+f"(d[59]), "+f"(d[60]), "+f"(d[61]), "+f"(d[62]), "+f"(d[63])
        : "l"(a), "l"(b), "r"(acc));
}

__device__ __forceinline__ void wgmma_rs_n32(float (&d)[16], const uint32_t (&a)[4], uint64_t b, int acc) {
    asm volatile("{ .reg .pred p; setp.ne.b32 p, %21, 0;\n"
        "wgmma.mma_async.sync.aligned.m64n32k16.f32.bf16.bf16 {%0,%1,%2,%3,%4,%5,%6,%7,%8,%9,%10,%11,%12,%13,%14,%15}, {%16,%17,%18,%19}, %20, p, 1, 1, 0; }"
        : "+f"(d[0]), "+f"(d[1]), "+f"(d[2]), "+f"(d[3]), "+f"(d[4]), "+f"(d[5]), "+f"(d[6]), "+f"(d[7]), "+f"(d[8]), "+f"(d[9]), "+f"(d[10]), "+f"(d[11]), "+f"(d[12]), "+f"(d[13]), "+f"(d[14]), "+f"(d[15])
        : "r"(a[0]), "r"(a[1]), "r"(a[2]), "r"(a[3]), "l"(b), "r"(acc));
}

__device__ __forceinline__ float warp_sum(float v) {
#pragma unroll
    for (int o = 16; o; o >>= 1) v += __shfl_xor_sync(0xffffffffu, v, o);
    return v;
}
__device__ __forceinline__ void ln_mod(const float (&xv)[20], const uint32_t (&sv)[10], const uint32_t (&tv)[10], float (&hv)[20]) {
    float s = 0;
#pragma unroll
    for (int i = 0; i < 20; i++) s += xv[i];
    const float mean = warp_sum(s) * (1.f / DM);
    float q = 0;
#pragma unroll
    for (int i = 0; i < 20; i++) { float d = xv[i] - mean; q += d * d; }
    const float mb = bfr(mean), inv = inv_std(warp_sum(q) * (1.f / DM));
#pragma unroll
    for (int i = 0; i < 10; i++) {
        const float n0 = bfr(bfr(xv[2 * i] - mb) * inv), n1 = bfr(bfr(xv[2 * i + 1] - mb) * inv);
        hv[2 * i] = bfr(bfr(n0 * bfr(1.f + lo_f(sv[i]))) + lo_f(tv[i]));
        hv[2 * i + 1] = bfr(bfr(n1 * bfr(1.f + hi_f(sv[i]))) + hi_f(tv[i]));
    }
}
__device__ __forceinline__ uint32_t ld_rlx(const uint32_t* f) { uint32_t v; asm volatile("ld.relaxed.gpu.global.u32 %0, [%1];" : "=r"(v) : "l"(f) : "memory"); return v; }
__device__ __forceinline__ void bump(uint32_t* f) { asm volatile("red.relaxed.gpu.global.add.u32 [%0], 1;" :: "l"(f) : "memory"); }
__device__ __forceinline__ void flag_wait(const uint32_t* f, uint32_t target) {
    for (int n = 0;; n++) {
        uint32_t v; asm volatile("ld.relaxed.gpu.global.u32 %0, [%1];" : "=r"(v) : "l"(f) : "memory");
        if (v >= target) break;
        if (n > (1 << 23)) __trap();
    }
}
__device__ __forceinline__ void flag_add(uint32_t* f, uint32_t v = 1) { asm volatile("red.release.gpu.global.add.u32 [%0], %1;" :: "l"(f), "r"(v) : "memory"); }
constexpr int N_SIDE = 36;
__device__ __forceinline__ void flags_release() {
    uint32_t old; asm volatile("atom.acq_rel.gpu.global.add.u32 %0, [%1], 1;" : "=r"(old) : "l"(&g_flags.done) : "memory");
    if (old == 96 + N_SIDE - 1) for (int i = 0; i < (int)(sizeof(Flags) / 16); i++) ((uint4*)&g_flags)[i] = make_uint4(0, 0, 0, 0);
}

struct ChainMaps { CUtensorMap wq, wk, wv, wo, h32, q32, k32, v32, wgate, wup, wdown, wmod; };
struct ChainArgs { const bf16 *x, *mem0, *c, *wv, *wo; bf16* out; int D1, D2, DG; };
constexpr uint32_t SM_BASE = 1024;
#define VGAP 20
#define XISS 4
#define XGAP 5
constexpr int NXR = 8;
constexpr int C_WV = 0, C_WO = 81920, C_XR = 167936, C_QX = C_XR + 2 * 4096, C_KX = C_XR + 3 * 4096, C_VX = C_XR + NXR * 4096, C_MEM = C_VX + 4096,
              C_QM = C_MEM + 10240, C_KM = C_QM + 1024, C_VP = C_KM + 1024, C_VM = C_VP + 4096, C_OX = C_VM + 1024, C_SC = C_OX + 3072, C_BAR = C_SC + 3840;
constexpr int CB_W = C_BAR, CB_W2 = C_BAR + 8, CB_SC = C_BAR + 16, CB_KX = C_BAR + 24, CB_VX = C_BAR + 32, CB_PRE = C_BAR + 40, CB_OX = C_BAR + 56, CB_VP = C_BAR + 64,
              CB_MEM = C_BAR + 80, CB_XF = C_BAR + 112, CB_XE = C_BAR + 176, C_PACE = C_BAR + 192;
constexpr int C_SMEM = C_BAR + 256;
#define PROF(i)
#define PROFG(i)
#define PROFV(i, v)
static_assert(C_SMEM <= 232448, "chain shared memory");
__device__ __forceinline__ uint32_t umax3(uint32_t a, uint32_t b, uint32_t c) { return max(max(a, b), c); }
__device__ __forceinline__ void wait_until(uint32_t t) { while ((int32_t)((uint32_t)clock() - t) < 0) {} }
__device__ __forceinline__ uint32_t gtime() { uint32_t c; asm volatile("mov.u32 %0, %%globaltimer_lo;" : "=r"(c)); return c; }
__device__ __forceinline__ uint32_t opaque(uint32_t v) { uint32_t r; asm volatile("shfl.sync.bfly.b32 %0, %1, 0, 31, -1;" : "=r"(r) : "r"(v)); return r; }
__device__ __forceinline__ uint32_t lds32(uint32_t a) { uint32_t v; asm volatile("ld.shared.u32 %0, [%1];" : "=r"(v) : "r"(a) : "memory"); return v; }
__device__ __forceinline__ float2 lds64f(uint32_t a) { float2 v; asm volatile("ld.shared.v2.f32 {%0,%1}, [%2];" : "=f"(v.x), "=f"(v.y) : "r"(a) : "memory"); return v; }
__device__ __forceinline__ float4 lds128f(uint32_t a) { float4 v; asm volatile("ld.shared.v4.f32 {%0,%1,%2,%3}, [%4];" : "=f"(v.x), "=f"(v.y), "=f"(v.z), "=f"(v.w) : "r"(a) : "memory"); return v; }
__device__ __forceinline__ void sts128f(uint32_t a, float x, float y, float z, float w) { asm volatile("st.shared.v4.f32 [%0], {%1,%2,%3,%4};" :: "r"(a), "f"(x), "f"(y), "f"(z), "f"(w) : "memory"); }
__device__ __forceinline__ uint32_t xor_or(uint32_t a, uint32_t b, uint32_t t) { uint32_t r; asm("lop3.b32 %0, %1, %2, %3, 0x7e;" : "=r"(r) : "r"(a), "r"(b), "r"(t)); return r; }
__device__ __forceinline__ uint32_t or3(uint32_t a, uint32_t b, uint32_t c) { uint32_t r; asm("lop3.b32 %0, %1, %2, %3, 0xfe;" : "=r"(r) : "r"(a), "r"(b), "r"(c)); return r; }
__device__ __forceinline__ int mem_forward(uint32_t sm, int s, int j, uint32_t u, uint32_t t0, uint32_t g0) {
    const uint32_t off = j * 896 + u * 16;
    const bool mine = u < 56 && off < 2560;
    uint32_t todo = mine ? 15u : 0u, open = 15u;
    const uint8_t* src = (const uint8_t*)(g_memg + s * 2560) + off;
    const uint32_t r1 = mapa(sm, (j + 1) % 3), r2 = mapa(sm, (j + 2) % 3);
    uint4 v[4];
#pragma unroll
    for (int p = 0; p < 4; p++) v[p] = make_uint4(0, 0, 0, 0);
    auto send = [&](int p) {
        asm volatile("{ .reg .u32 a, b;\n"
            "add.u32 a, %0, %5; add.u32 b, %5, %8; st.async.shared::cluster.mbarrier::complete_tx::bytes.v4.b32 [a], {%1,%2,%3,%4}, [b];\n"
            "add.u32 a, %0, %6; add.u32 b, %6, %8; st.async.shared::cluster.mbarrier::complete_tx::bytes.v4.b32 [a], {%1,%2,%3,%4}, [b];\n"
            "add.u32 a, %0, %7; st.shared.v4.b32 [a], {%1,%2,%3,%4}; }"
            :: "r"(off + (C_MEM + p * 2560)), "r"(v[p].x), "r"(v[p].y), "r"(v[p].z), "r"(v[p].w), "r"(r1), "r"(r2), "r"(sm), "r"(CB_MEM + 8 * p) : "memory");
    };
    if (g0) { while ((int32_t)(gtime() - g0) < 0 && (int32_t)((uint32_t)clock() - t0) < 4000) {} }
    else wait_until(t0);
    for (int n = 0;; n++) {
#pragma unroll
        for (int p = 0; p < 4; p++)
            asm volatile("{ .reg .pred q; setp.ne.u32 q, %5, 0;\n@q ld.relaxed.gpu.global.v4.u32 {%0,%1,%2,%3}, [%4]; }"
                : "+r"(v[p].x), "+r"(v[p].y), "+r"(v[p].z), "+r"(v[p].w) : "l"(src + p * 2560), "r"(todo & (1u << p)) : "memory");
        uint32_t miss = 0;
#pragma unroll
        for (int p = 0; p < 4; p++) miss |= (umax3(umax3(v[p].x, v[p].y, v[p].z), v[p].w, 0u) == 0xffffffffu ? 1u : 0u) << p;
        if (n == 0 && !__any_sync(0xffffffffu, miss)) {
            if (mine) { send(0); send(1); send(2); send(3); }
            __syncwarp();
            if ((u & 31) < 4) mbar_arrive(sm + CB_MEM + 8 * (u & 31));
            return 0;
        }
        const uint32_t ok = todo & ~miss;
#pragma unroll
        for (int p = 0; p < 4; p++) if (ok & (1u << p)) send(p);
        todo &= miss;
        __syncwarp();
        const uint32_t left = __reduce_or_sync(0xffffffffu, todo);
        if ((u & 31) < 4 && ((open & ~left) >> (u & 31) & 1)) mbar_arrive(sm + CB_MEM + 8 * (u & 31));
        open = left;
        if (!left) return n;
        if (n > SPIN_LIMIT) __trap();
    }
}
__device__ __forceinline__ void wgmma_ss_n8_ta(float (&d)[4], uint64_t a, uint64_t b) {
    asm volatile("wgmma.mma_async.sync.aligned.m64n8k16.f32.bf16.bf16 {%0,%1,%2,%3}, %4, %5, 1, 1, 1, 1, 0;"
        : "+f"(d[0]), "+f"(d[1]), "+f"(d[2]), "+f"(d[3]) : "l"(a), "l"(b));
}
__device__ __forceinline__ void wgmma_ss_n8_ta_first(float (&d)[4], uint64_t a, uint64_t b) {
    asm volatile("wgmma.mma_async.sync.aligned.m64n8k16.f32.bf16.bf16 {%0,%1,%2,%3}, %4, %5, 0, 1, 1, 1, 0;"
        : "=f"(d[0]), "=f"(d[1]), "=f"(d[2]), "=f"(d[3]) : "l"(a), "l"(b));
}
__device__ __forceinline__ void score_tile(const uint32_t (&qa)[4][4], const uint32_t (&kb)[2][4], bool odd, float (&x)[4]) {
    float sc[2][4] = {{0, 0, 0, 0}, {0, 0, 0, 0}};
#pragma unroll
    for (int k = 0; k < 4; k++) mma16(sc[k & 1], qa[k][0], qa[k][1], qa[k][2], qa[k][3], kb[k >> 1][2 * (k & 1)], kb[k >> 1][2 * (k & 1) + 1]);
    float a = sc[0][0] + sc[1][0], b = sc[0][1] + sc[1][1];
    float c = __shfl_xor_sync(0xffffffffu, a, 1), d = __shfl_xor_sync(0xffffffffu, b, 1);
    x[0] = odd ? c : a; x[1] = odd ? d : b; x[2] = odd ? a : c; x[3] = odd ? b : d;
}
__device__ __forceinline__ void send_piece(const float (&x)[4], uint32_t rdst, uint32_t rbar, uint32_t ldst) {
    asm volatile("st.async.shared::cluster.mbarrier::complete_tx::bytes.v4.f32 [%0], {%1,%2,%3,%4}, [%5];"
        :: "r"(rdst), "f"(x[0]), "f"(x[1]), "f"(x[2]), "f"(x[3]), "r"(rbar) : "memory");
    sts128f(ldst, x[0], x[1], x[2], x[3]);
}

__device__ __forceinline__ void x_part(const uint32_t (&wa)[40][4], const ChainMaps& mp, uint32_t sm, int n, int wg, int w, uint32_t ln, int col0, int j) {
    const int s = n - 1; const bool lane0 = ln == 0; (void)s; (void)lane0;
    float acc[16];
#pragma unroll
    for (int i = 0; i < 16; i++) acc[i] = 0.f;
    const bool issuer = wg == 1 && w == 1 && ln == 0;
    const uint64_t xd = mkdesc(SM_BASE + C_XR, 16, 1024);
    if (wg == 0 && w == 0) PROF(12);
    mbar_wait(sm + CB_XF, n & 1);
#pragma unroll
    for (int c = 0; c < 10; c++) {
        if (c >= NXR) mbar_wait(sm + CB_XF + 8 * (1 + c - NXR), n & 1);
        if (c == XGAP && n > 0) bar_sync(9, 288);
        WG_FENCE();
#pragma unroll
        for (int ks = 0; ks < 4; ks++)
            wgmma_rs_n32(acc, wa[4 * c + ks], xd + (((c % NXR) * 4096 + ks * 32) >> 4), 1);
        if (c <= 10 - NXR) {
            WG_COMMIT();
            if (c >= 1) {
                WG_WAIT(1);
                if (w == 0 && ln == 0) mbar_arrive_remote(mapa(sm + CB_XE + 8 * (c - 1), c - 1));
                __syncwarp();
            }
        }
        if (c == XISS - 1) {
            if (issuer) {
#pragma unroll
                for (int f = 0; f < 10 - NXR; f++) mbar_expect(sm + CB_XF + 8 * (1 + f), 4096);
                if (j < 10 - NXR) {
                    mbar_wait(sm + CB_XE + 8 * j, n & 1);
                    tma2d_mc(sm + C_XR + j * 4096, &mp.h32, (j + NXR) * 64, n * SEG, sm + CB_XF + 8 * (1 + j), 7);
                }
            }
            __syncwarp();
        }
    }
    WG_COMMIT();
    WG_WAIT(0);
    if (wg == 0 && w == 0) PROF(30);
    bar_sync(8, 256);
    const uint32_t r = ln & 7, mi = ln >> 3, dst = sm + (wg == 0 ? C_QX : C_KX) + ((mi >> 1) * 8 + r) * 128 + (((2 * w + (mi & 1)) ^ r) << 4);
#pragma unroll
    for (int p = 0; p < 2; p++)
        stsm4t(dst + p * 2048, pack2(acc[8 * p], acc[8 * p + 1]), pack2(acc[8 * p + 2], acc[8 * p + 3]), pack2(acc[8 * p + 4], acc[8 * p + 5]), pack2(acc[8 * p + 6], acc[8 * p + 7]));
    asm volatile("fence.proxy.async.shared::cta;" ::: "memory");
    bar_sync(6 + wg, 128);
    if (w == 0 && ln == 0) {
        if (wg == 1) mbar_arrive(sm + CB_KX);
        tma2d_store(wg == 0 ? &mp.q32 : &mp.k32, col0, n * SEG, sm + (wg == 0 ? C_QX : C_KX));
        asm volatile("cp.async.bulk.commit_group;" ::: "memory");
    }
    __syncwarp();
}
__device__ __forceinline__ void x_prefetch(const ChainMaps& mp, uint32_t sm, int n, int j) {
    mbar_expect(sm + CB_XF, NXR * 4096);
#pragma unroll
    for (int c = 0; c < 3; c++)
        if (3 * c + j < NXR) tma2d_mc(sm + C_XR + (3 * c + j) * 4096, &mp.h32, (3 * c + j) * 64, n * SEG, sm + CB_XF, 7);
    if (blockIdx.x < 10 - NXR)
        tma2d_prefetch(&mp.h32, (NXR + (int)blockIdx.x) * 64, n * SEG);
}

__global__ void __cluster_dims__(3, 1, 1) __launch_bounds__(384, 1) k_chain(const __grid_constant__ ChainMaps mp, const __grid_constant__ ChainArgs ar) {
    const int D1 = ar.D1, D2 = ar.D2, DG = ar.DG;
    extern __shared__ __align__(1024) uint8_t smraw[];
    const uint32_t sm = SM_BASE + ((blockIdx.x % 3) << 24);
    if (smem_u32(smraw) != sm) __trap();
    uint32_t tid; asm volatile("mov.u32 %0, %%tid.x;" : "=r"(tid));
    const int warp = __shfl_sync(0xffffffffu, tid >> 5, 0), lane = tid & 31, wg = warp >> 2, w = warp & 3;
    const int blk = blockIdx.x, head = blk / 3, j = blk % 3;
    const int col0 = head * DH + j * 64;
    const int mt0 = j == 0 ? 0 : j == 1 ? 14 : 27, nmt = j == 0 ? 14 : 13;
    asm volatile("griddepcontrol.launch_dependents;");
#define PPROF(i)
    {
        const int mc0 = (blk >> 1) * 80 + (blk & 1) * 32, mcn = (blk & 1) ? 24 : 16;
        const int nrow = blk < 74 ? 2 : blk == 74 ? (warp < 8 ? 2 : 1) : 1;
        if (tid == 0) {
            mbar_init(sm + CB_PRE, 1);
            asm volatile("fence.mbarrier_init.release.cluster;" ::: "memory");
            const int n1 = blk < 74 ? 15360 : blk == 74 ? 10240 : 0;
            mbar_expect(sm + CB_PRE, 61440 + 1280 + 15360 + n1);
            bulk_g2s(sm + C_QM, ar.c, 1280, sm + CB_PRE);
#pragma unroll 1
            for (int c = 0; c < 4; c++) tma2d(sm + C_WO + 24576 + c * 15360, &mp.wmod, mc0, c * 160, sm + CB_PRE);
            bulk_g2s(sm + C_XR, ar.x + blk * 12 * DM, 15360, sm + CB_PRE);
            if (n1) bulk_g2s(sm + C_XR + 15360, ar.x + (1152 + blk * 12) * DM, n1, sm + CB_PRE);
        }
        if (tid == 32) {
#pragma unroll 1
            for (int c = 0; c < 24; c++) if (c != 5) mbar_init(sm + C_BAR + 8 * c, c == 2 || c == 7 ? 5 : c == 8 ? 8 : (c >= 10 && c < 14) ? 3 : c >= 22 ? 6 : 1);
            asm volatile("fence.mbarrier_init.release.cluster;" ::: "memory");
            mbar_expect(sm + CB_SC, 2560); mbar_expect(sm + CB_OX, 2048);
#pragma unroll 1
            for (int c = 0; c < 4; c++) mbar_expect(sm + CB_MEM + 8 * c, j == 2 ? 2560 - 768 : 2560 - 896);
        }
#pragma unroll 1
        for (int i = blk * 384 + tid; i < NSEG * 640; i += 96 * 384)
            ((uint4*)g_memg)[i] = i < 640 ? __ldg((const uint4*)(ar.mem0 + (i & 7) * DM + (i >> 3) * 8)) : make_uint4(~0u, ~0u, ~0u, ~0u);
        if (blk * 384 + tid < 80 * 32 * 8) ((uint4*)g_part)[blk * 384 + tid] = make_uint4(0, 0, 0, 0);
        PPROF(8);
        asm volatile("barrier.cluster.arrive.release.aligned; barrier.cluster.wait.acquire.aligned;" ::: "memory");
        PPROF(9);
        mbar_wait(sm + CB_PRE, 0);
        PPROF(10);
        if (tid == 352) {
            const uint64_t ef = policy_stream();
            mbar_expect(sm + CB_W, 2 * 81920);
#pragma unroll 1
            for (int c = 0; c < 10; c++) tma2d_ef(sm + C_WV + c * 8192, &mp.wq, col0, c * 64, sm + CB_W, ef);
        }
        if (tid < 320) {
            const uint32_t cv = lds32(sm + C_QM + tid * 4);
            asm volatile("st.shared.v2.f32 [%0], {%1,%2};" :: "r"(sm + C_VP + tid * 8), "f"(bfr(__fdividef(lo_f(cv), 1.f + __expf(-lo_f(cv))))),
                         "f"(bfr(__fdividef(hi_f(cv), 1.f + __expf(-hi_f(cv))))) : "memory");
        }
        __syncthreads();
        {
            float a0 = 0, a1 = 0;
            const uint32_t k0 = (tid / 24) * 40, wa0 = sm + C_WO + 24576 + k0 * 96 + (tid % 24) * 4;
#pragma unroll 4
            for (int i = 0; i < 40; i++) {
                const float sc = __uint_as_float(lds32(sm + C_VP + (k0 + i) * 4));
                const uint32_t wv = lds32(wa0 + i * 96);
                a0 += sc * lo_f(wv); a1 += sc * hi_f(wv);
            }
            asm volatile("st.shared.v2.f32 [%0], {%1,%2};" :: "r"(sm + C_MEM + tid * 8), "f"(a0), "f"(a1) : "memory");
        }
        __syncthreads();
        PPROF(11);
        if (warp == 0) {
            float a0 = 0, a1 = 0;
            const int cp = lane < mcn ? lane : 0;
#pragma unroll 4
            for (int i = 0; i < 16; i++) { const float2 v = lds64f(sm + C_MEM + (i * 24 + cp) * 8); a0 += v.x; a1 += v.y; }
            uint32_t* dst = (uint32_t*)(g_mod + mc0) + cp;
            *dst = pack2(a0, a1);
            const uint32_t rb = ld_rlx(dst);
            PPROF(1);
            if (__all_sync(0xffffffffu, rb == pack2(a0, a1)) && tid == 0) bump(blk < 32 ? &g_flags.mod : &g_flags.h);
            if (tid == 0) flag_wait(&g_flags.mod, 32);
            PPROF(2);
        }
        __syncthreads();
        uint32_t sv[10], tv[10], bad = 0;
#pragma unroll
        for (int i = 0; i < 10; i++) { sv[i] = __ldcg((const uint32_t*)g_mod + DM / 2 + lane + 32 * i); tv[i] = __ldcg((const uint32_t*)g_mod + lane + 32 * i); }
#pragma unroll 1
        for (int q = 0; q < nrow; q++) {
            float xv[20], hv[20];
#pragma unroll
            for (int i = 0; i < 10; i++) { const uint32_t v = lds32(sm + C_XR + q * 15360 + warp * 1280 + lane * 4 + i * 128); xv[2 * i] = lo_f(v); xv[2 * i + 1] = hi_f(v); }
            ln_mod(xv, sv, tv, hv);
            uint32_t* dst = (uint32_t*)g_h + (q * 1152 + blk * 12 + warp) * (DM / 2) + lane;
#pragma unroll
            for (int i = 0; i < 10; i++) dst[32 * i] = pack2(hv[2 * i], hv[2 * i + 1]);
#pragma unroll
            for (int i = 0; i < 10; i++) bad |= ld_rlx(dst + 32 * i) ^ pack2(hv[2 * i], hv[2 * i + 1]);
        }
        if (__syncthreads_or(bad)) __trap();
        PPROF(3);
        if (tid == 0) {
            bump(&g_flags.h);
            flag_wait(&g_flags.h, 160);
            x_prefetch(mp, sm, 0, j);
            const uint64_t ef = policy_stream();
#pragma unroll 1
            for (int c = 0; c < 10; c++) tma2d_ef(sm + C_WO + c * 8192, &mp.wk, col0, c * 64, sm + CB_W, ef);
        }
        PPROF(4);
        __syncthreads();
        if (tid >= 64) {
#pragma unroll 1
            for (int i = tid - 64; i < 640 + 192 * 4; i += 320)
                asm volatile("prefetch.global.L2 [%0];" :: "l"(i < 640 ? ar.wv + (size_t)i * HD + col0 : ar.wo + (size_t)(head * DH + ((i - 640) >> 2)) * DM + mt0 * 16 + min((i & 3) * 64, 639 - mt0 * 16)));
        }
    }
    const int r = lane & 7, mi = lane >> 3;
    const uint32_t memrd = opaque(sm + C_MEM + lane * 16);
    const bool lane0 = (memrd & 0x1f0) == 0;
    if (wg < 2) {
        asm volatile("setmaxnreg.inc.sync.aligned.u32 208;");
        uint32_t wa[40][4];
        mbar_wait(sm + CB_W, 0);
#pragma unroll
        for (int ks = 0; ks < 40; ks++) ldsm4t(wa[ks], sm + (wg == 0 ? C_WV : C_WO) + ((mi >> 1) * 8 + r) * 128 + (((2 * w + (mi & 1)) ^ r) << 4) + ks * 2048);
        PPROF(5);
        bar_sync(1, 384);
        x_part(wa, mp, sm, 0, wg, w, lane, col0, j);
        PPROF(6);
        mbar_wait(sm + CB_W2, 0);
        PPROF(7);
        const uint32_t qst = opaque(sm + (wg == 0 ? C_QM : C_KM) + (2 * w + (mi & 1)) * 128 + r * 16);
        if (warp == 5 && lane0) {
            flag_wait(&g_flags.v[head], 2);
            mbar_expect(sm + CB_VX, 4096);
            tma2d(sm + C_VX, &mp.v32, col0, 0, sm + CB_VX);
        }
        __syncwarp();
        const uint64_t vda = mkdesc(SM_BASE + C_WV + wg * 40960, 8192, 1024);
        const uint64_t vdb = (uint64_t)(((SM_BASE + C_MEM + wg * 5120) & 0x3FFFF) >> 4) | ((uint64_t)(128 >> 4) << 16) | ((uint64_t)(256 >> 4) << 32);
        for (int s = 0; s < NSEG; s++) {
            float res[4];
            mbar_wait(sm + CB_MEM, s & 1);
            if (warp == 0) { PROF(0); PROFG(24); }
            {
                float d[4][4];
#pragma unroll
                for (int c = 0; c < 4; c++) { d[c][0] = d[c][1] = d[c][2] = d[c][3] = 0.f; }
                uint32_t b[4][4];
#pragma unroll
                for (int k = 0; k < 3; k++) ldsm4(b[k], memrd + k * 512);
                bool rdy = mbar_test(sm + CB_MEM + 8, s & 1);
#pragma unroll
                for (int k2 = 0; k2 < 20; k2++) {
                    if (k2 + 3 < 20) {
                        if ((k2 + 3) % 5 == 0) {
                            if (!rdy) mbar_wait(sm + CB_MEM + 8 * ((k2 + 3) / 5), s & 1);
                            if (k2 + 8 < 20) rdy = mbar_test(sm + CB_MEM + 8 * ((k2 + 8) / 5), s & 1);
                        }
                        ldsm4(b[(k2 + 3) & 3], memrd + (k2 + 3) * 512);
                    }
                    mma16(d[(2 * k2) & 3], wa[2 * k2][0], wa[2 * k2][1], wa[2 * k2][2], wa[2 * k2][3], b[k2 & 3][0], b[k2 & 3][1]);
                    mma16(d[(2 * k2 + 1) & 3], wa[2 * k2 + 1][0], wa[2 * k2 + 1][1], wa[2 * k2 + 1][2], wa[2 * k2 + 1][3], b[k2 & 3][2], b[k2 & 3][3]);
                }
#pragma unroll
                for (int i = 0; i < 4; i++) res[i] = (d[0][i] + d[1][i]) + (d[2][i] + d[3][i]);
            }
            const uint32_t p0 = pack2(res[0], res[1]), p1 = pack2(res[2], res[3]);
            stsm2t(qst, p0, p1);
            if (w == 0 && lane0) asm volatile("cp.async.bulk.wait_group.read 0;" ::: "memory");
            bar_arrive(2, 384);
            if (w == 0) PROF(1 + wg);
            {
                float d[2][4];
                asm volatile("fence.proxy.async.shared::cta;" ::: "memory");
                bar_sync(4, 384);
                WG_FENCE();
                wgmma_ss_n8_ta_first(d[0], vda, vdb); wgmma_ss_n8_ta_first(d[1], vda + (2048 >> 4), vdb + (256 >> 4));
#pragma unroll
                for (int ks = 2; ks < 20; ks++) {
                    if (ks == VGAP) { bar_sync(11, 384); WG_FENCE(); }
                    wgmma_ss_n8_ta(d[ks & 1], vda + ks * (2048 >> 4), vdb + ks * (256 >> 4));
                }
                WG_COMMIT(); WG_WAIT(0);
                sts128f(memrd + (C_VP - C_MEM) + warp * 512, d[0][0] + d[1][0], d[0][1] + d[1][1], d[0][2] + d[1][2], d[0][3] + d[1][3]);
                __syncwarp();
                if (lane0) mbar_arrive(sm + CB_VP);
            }
            if (warp == 0) PROF(7);
            const uint32_t ln = opaque(memrd) >> 4 & 31;
            if (ln == 0 && s + 1 < NSEG) {
                if (warp == 5) {
                    if ((s & 3) == 3) { flag_wait(&g_flags.v[((s + 1) >> 2) * 32 + head], 2); }
                    mbar_expect(sm + CB_VX, 4096);
                    tma2d(sm + C_VX, &mp.v32, col0, (s + 1) * SEG, sm + CB_VX);
                }
                if (warp == 1) {
                    mbar_wait(sm + CB_SC, s & 1);
                    x_prefetch(mp, sm, s + 1, j);
                }
            }
            if (w == 0 && ln == 0) {
                asm volatile("cp.async.bulk.wait_group 0;" ::: "memory");
            }
            bar_sync(5, 384);
            {
                uint32_t f0 = p0, f1 = p1;
                if (wg == 0) asm volatile("ld.shared.v2.u32 {%0,%1}, [%2];" : "=r"(f0), "=r"(f1) : "r"(sm + C_VM + w * 256 + ln * 8) : "memory");
                const uint32_t t0_ = movm_t(f0), t1_ = movm_t(f1);
                uint8_t* dst = (uint8_t*)(wg == 0 ? g_vm : g_km) + (size_t)s * (NH * 8 * DH * 2) + ((head * 8 + (ln >> 2)) * DH + j * 64 + 16 * w + (ln & 3) * 2) * 2;
                *(uint32_t*)dst = t0_; *(uint32_t*)(dst + 16) = t1_;
            }
            if (s + 1 < NSEG) x_part(wa, mp, sm, s + 1, wg, w, ln, col0, j);
            else {
                bar_sync(6 + wg, 128);
                if (w == 0 && ln == 0) flag_add(&g_flags.seg[63 * 32 + head], 1);
            }
            if (warp == 0) PROF(11);
        }
    } else {
        asm volatile("setmaxnreg.dec.sync.aligned.u32 88;");
        bar_sync(1, 384);
        if (tid == 256) {
            mbar_expect(sm + CB_W2, 81920 + 86016);
#pragma unroll 1
            for (int c = 0; c < 10; c++) tma2d(sm + C_WV + c * 8192, &mp.wv, col0, c * 64, sm + CB_W2);
#pragma unroll 1
            for (int c = 0; c < 7; c++) tma2d(sm + C_WO + c * 12288, &mp.wo, mt0 * 16 + c * 32, head * DH, sm + CB_W2);
        }
        mbar_wait(sm + CB_W2, 0);
        const int oc = blk % 80;
        const float scale = 0.07216878364870322f;
        if (w >= 2) mem_forward(sm, 0, j, tid - 320, clock(), 0);
        for (int s = 0; s < NSEG; s++) {
            const uint32_t l0 = opaque(memrd) >> 4 & 31, r0 = l0 & 7, m0 = l0 >> 3;
            const uint32_t vkey = 16 * (m0 >> 1) + 4 * (r0 >> 1) + 2 * (m0 & 1) + (r0 & 1);
            const uint32_t vxrd = sm + C_VX + vkey * 128 + (((2 * w) ^ (vkey & 7)) << 4);
            const uint32_t kxrd = sm + C_KX + (8 * w + r0) * 128 + ((m0 ^ r0) << 4);
            const uint32_t sco = (w >> 1) * 512 + (l0 >> 2) * 64 + (w & 1) * 32 + ((l0 >> 1) & 1) * 16, peer = (j + 1 + (l0 & 1)) % 3;
            const uint32_t word = opaque(sm + C_WO + (w >> 1) * 12288 + ((m0 >> 1) * 8 + r0) * 64 + ((((w & 1) * 2 + (m0 & 1)) ^ (r0 >> 1)) << 4));
            const uint32_t qrd = opaque(sm + C_QM + (m0 >> 1) * 128 + r0 * 16);
            const uint32_t scdst = opaque(sm + C_SC + j * 1280 + sco);
            const uint32_t rbase = opaque(mapa(sm, peer) - sm);
            const uint32_t scm = opaque(1024 + (l0 >> 1) * 16 - sco);
            const uint32_t oxrd = opaque(sm + C_OX + l0 * 8);
            const uint32_t poff = opaque(((2 * (mt0 + w) * 32 + head) * 32 + l0) * 4);
            uint32_t kb[2][4], vb[2][4];
            mbar_wait(sm + CB_KX, s & 1);
            ldsm4(kb[0], kxrd); ldsm4(kb[1], kxrd ^ 64);
            mbar_wait(sm + CB_VX, s & 1);
            ldsm4t(vb[0], vxrd); ldsm4t(vb[1], vxrd ^ 16);
            bar_sync(2, 384);
            const bool odd = memrd & 16;
            {
                uint32_t qa[4][4];
#pragma unroll
                for (int k = 0; k < 4; k++) ldsm4(qa[k], qrd + k * 256);
                float x[4];
                if (w == 3) {
                    uint32_t km[2][4]; float y[4];
                    ldsm4(km[0], memrd + (C_KM - C_MEM)); ldsm4(km[1], memrd + (C_KM - C_MEM) + 512);
                    score_tile(qa, kb, odd, x); score_tile(qa, km, odd, y);
                    if (s + 1 < NSEG) { send_piece(x, scdst + rbase, sm + CB_SC + rbase, scdst); send_piece(y, scdst + scm + rbase, sm + CB_SC + rbase, scdst + scm); }
                } else {
                    score_tile(qa, kb, odd, x);
                    if (s + 1 < NSEG) send_piece(x, scdst + rbase, sm + CB_SC + rbase, scdst);
                }
                bar_arrive(4, 384);
            }
            if (s + 1 == NSEG) {
                if (VGAP < 20) bar_arrive(11, 384);
                if (w == 1 && lane0) flag_add(&g_flags.seg[62 * 32 + head], 2);
                mbar_wait(sm + CB_VP, s & 1);
                const uint32_t vp = memrd + (C_VP - C_MEM) + w * 512;
                float4 y0 = lds128f(vp), y1 = lds128f(vp + 2048);
                asm volatile("st.shared.v2.u32 [%0], {%1,%2};" :: "r"(oxrd - (C_OX - C_VM) + w * 256), "r"(pack2(y0.x + y1.x, y0.y + y1.y)), "r"(pack2(y0.z + y1.z, y0.w + y1.w)) : "memory");
                bar_arrive(5, 384);
                break;
            }
            __syncwarp();
            if (lane0) mbar_arrive(sm + CB_SC);
            if (w == 0) PROF(4);
            mbar_wait(sm + CB_SC, s & 1);
            if (w == 0) PROF(8);
            float sv[10];
            {
                const uint32_t scrd = memrd + (C_SC - C_MEM);
                float4 x[3], y[3]; float2 z[3];
#pragma unroll
                for (int p = 0; p < 3; p++) { x[p] = lds128f(scrd + p * 1280); y[p] = lds128f(scrd + p * 1280 + 512); z[p] = lds64f(oxrd + (C_SC - C_OX) + p * 1280 + 1024); }
                sv[0] = (x[0].x + x[1].x) + x[2].x; sv[1] = (x[0].y + x[1].y) + x[2].y; sv[2] = (x[0].z + x[1].z) + x[2].z; sv[3] = (x[0].w + x[1].w) + x[2].w;
                sv[4] = (y[0].x + y[1].x) + y[2].x; sv[5] = (y[0].y + y[1].y) + y[2].y; sv[6] = (y[0].z + y[1].z) + y[2].z; sv[7] = (y[0].w + y[1].w) + y[2].w;
                sv[8] = (z[0].x + z[1].x) + z[2].x; sv[9] = (z[0].y + z[1].y) + z[2].y;
            }
            float mx = fmaxf(fmaxf(fmaxf(sv[0], sv[1]), fmaxf(sv[2], sv[3])), fmaxf(fmaxf(fmaxf(sv[4], sv[5]), fmaxf(sv[6], sv[7])), fmaxf(sv[8], sv[9])));
            mx = fmaxf(mx, __shfl_xor_sync(0xffffffffu, mx, 1)); mx = fmaxf(mx, __shfl_xor_sync(0xffffffffu, mx, 2));
            if (VGAP < 20) {
                asm volatile("st.shared.f32 [%0], %1; bar.arrive 11, 384;" :: "r"(qrd), "f"(mx) : "memory");
            }
            const float sl2e = scale * 1.4426950408889634f, mxl = mx * sl2e;
#pragma unroll
            for (int i = 0; i < 10; i++) asm("ex2.approx.ftz.f32 %0, %1;" : "=f"(sv[i]) : "f"(fmaf(sv[i], sl2e, -mxl)));
            uint32_t pa[5];
#pragma unroll
            for (int i = 0; i < 5; i++) pa[i] = pack2(sv[2 * i], sv[2 * i + 1]);
            float sum = ((sv[0] + sv[1]) + (sv[2] + sv[3])) + ((sv[4] + sv[5]) + (sv[6] + sv[7])) + (sv[8] + sv[9]);
            if (w == 0) PROF(6);
            mbar_wait(sm + CB_VP, s & 1);
            uint32_t vm0, vm1;
            {
                const uint32_t vp = memrd + (C_VP - C_MEM) + w * 512;
                float4 y0 = lds128f(vp), y1 = lds128f(vp + 2048);
                float o[2][4] = {{0, 0, 0, 0}, {0, 0, 0, 0}}, o2[2][4] = {{0, 0, 0, 0}, {0, 0, 0, 0}};
#pragma unroll
                for (int u = 0; u < 2; u++) mma16(o[u], pa[0], pa[0], pa[1], pa[1], vb[u][0], vb[u][1]);
#pragma unroll
                for (int u = 0; u < 2; u++) mma16(o2[u], pa[2], pa[2], pa[3], pa[3], vb[u][2], vb[u][3]);
                sum += __shfl_xor_sync(0xffffffffu, sum, 1);
                vm0 = pack2(y0.x + y1.x, y0.y + y1.y); vm1 = pack2(y0.z + y1.z, y0.w + y1.w);
                sum += __shfl_xor_sync(0xffffffffu, sum, 2);
                mma8(o[0], pa[4], pa[4], vm0); mma8(o[1], pa[4], pa[4], vm1);
                float inv; asm("rcp.approx.ftz.f32 %0, %1;" : "=f"(inv) : "f"(sum));
                const uint32_t a = pack2((o[0][0] + o2[0][0]) * inv, (o[0][1] + o2[0][1]) * inv), b = pack2((o[1][0] + o2[1][0]) * inv, (o[1][1] + o2[1][1]) * inv);
                const uint32_t c = __shfl_xor_sync(0xffffffffu, a, 1), d = __shfl_xor_sync(0xffffffffu, b, 1);
                const float x[4] = {__uint_as_float(odd ? c : a), __uint_as_float(odd ? d : b), __uint_as_float(odd ? a : c), __uint_as_float(odd ? b : d)};
                const uint32_t od = (oxrd & ~8u) + (4 * j + w) * 256;
                send_piece(x, od + rbase, sm + CB_OX + rbase, od);
                __syncwarp();
                if (lane0) mbar_arrive(sm + CB_OX);
            }
            asm volatile("st.shared.v2.u32 [%0], {%1,%2};" :: "r"(oxrd - (C_OX - C_VM) + w * 256), "r"(vm0), "r"(vm1) : "memory");
            if (w == 0) PROF(10);
            uint32_t a[8][4];
            const uint32_t wl = word + (6 - (w >> 1)) * 12288 + w * 3072;
#pragma unroll
            for (int k = 0; k < 3; k++) { ldsm4t(a[k], wl + k * 1024); ldsm4t(a[3 + k], (wl ^ 32) + k * 1024); }
#pragma unroll
            for (int k = 0; k < 2; k++) ldsm4t(a[6 + k], word + k * 1024);
            mbar_wait(sm + CB_OX, s & 1);
            uint32_t ol[3][2], ob[12][2];
#pragma unroll
            for (int k = 0; k < 3; k++) asm volatile("ld.shared.v2.u32 {%0,%1}, [%2];" : "=r"(ol[k][0]), "=r"(ol[k][1]) : "r"(oxrd + w * 768 + k * 256) : "memory");
#pragma unroll
            for (int k = 0; k < 12; k++) asm volatile("ld.shared.v2.u32 {%0,%1}, [%2];" : "=r"(ob[k][0]), "=r"(ob[k][1]) : "r"(oxrd + k * 256) : "memory");
            if (w == 0) PROF(9);
            const uint32_t tag = (s & 1) ^ 1;
            uint8_t* pdst = (uint8_t*)g_part + poff;
            const uint32_t lp = memrd + (C_VP - C_MEM);
            {
                float e[2][4] = {{0, 0, 0, 0}, {0, 0, 0, 0}};
#pragma unroll
                for (int k = 0; k < 3; k++) {
                    mma16(e[0], a[k][0], a[k][1], a[k][2], a[k][3], ol[k][0], ol[k][1]);
                    mma16(e[1], a[3 + k][0], a[3 + k][1], a[3 + k][2], a[3 + k][3], ol[k][0], ol[k][1]);
                    ldsm4t(a[k], word + (2 + k) * 1024); ldsm4t(a[3 + k], word + (5 + k) * 1024);
                }
                sts128f(lp + (w & 1) * 2048 + w * 512, e[0][0], e[0][1], e[0][2], e[0][3]);
                sts128f(lp + ((w & 1) ^ 1) * 2048 + w * 512, e[1][0], e[1][1], e[1][2], e[1][3]);
            }
#pragma unroll
            for (int q = 0; q < 3; q++) {
                float e[2][4] = {{0, 0, 0, 0}, {0, 0, 0, 0}};
#pragma unroll
                for (int k = 0; k < 12; k++) {
                    const int i = q * 12 + k, n = i + 8, sl = (i + 6) & 7;
                    mma16(e[k & 1], a[sl][0], a[sl][1], a[sl][2], a[sl][3], ob[k][0], ob[k][1]);
                    if (n < 36) ldsm4t(a[sl], word + (n / 12) * 24576 + (n % 12) * 1024);
                }
#pragma unroll
                for (int hf = 0; hf < 2; hf++)
                    asm volatile("st.relaxed.gpu.global.u32 [%0], %1;" :: "l"(pdst + (8 * q + hf) * (32 * 128)),
                        "r"((pack2(e[0][2 * hf] + e[1][2 * hf], e[0][2 * hf + 1] + e[1][2 * hf + 1]) & ~1u) | tag) : "memory");
                if (q == 0) {
                    bar_sync(3, 128);
                    if (12 + w < nmt) {
                        float4 y0 = lds128f(lp + w * 2048), y1 = lds128f(lp + w * 2048 + 512), y2 = lds128f(lp + w * 2048 + 1024), y3 = lds128f(lp + w * 2048 + 1536);
                        asm volatile("st.relaxed.gpu.global.u32 [%0], %1;" :: "l"(pdst + 24 * (32 * 128)), "r"((pack2((y0.x + y1.x) + (y2.x + y3.x), (y0.y + y1.y) + (y2.y + y3.y)) & ~1u) | tag) : "memory");
                        asm volatile("st.relaxed.gpu.global.u32 [%0], %1;" :: "l"(pdst + 25 * (32 * 128)), "r"((pack2((y0.z + y1.z) + (y2.z + y3.z), (y0.w + y1.w) + (y2.w + y3.w)) & ~1u) | tag) : "memory");
                    }
                }
            }
            const uint32_t tw = clock();
            bar_arrive(5, 384);
            if (w == 0) { PROF(14); PROFG(25); }
            const uint32_t ln = opaque(memrd) >> 4 & 31, gg = ln >> 2, tt = ln & 3;
            if (w == 0) {
                const uint8_t* src = (const uint8_t*)g_part + ((oc * 32 + tt) * 8 + gg) * 16;
                uint32_t* mdst = g_memg + (s + 1) * 2560 + oc * 32 + ln;
                const uint32_t sel0 = gg == 0 ? 0x00003f80u : gg == 1 ? 0x3f800000u : 0u, sel1 = gg == 2 ? 0x00003f80u : gg == 3 ? 0x3f800000u : 0u;
                const uint32_t sl = (ln & 28) | (tt >> 1);
                wait_until(tw + D1);
                for (int n = 0;; n++) {
                    uint4 v[8];
#pragma unroll
                    for (int i = 0; i < 8; i++)
                        asm volatile("ld.relaxed.gpu.global.v4.u32 {%0,%1,%2,%3}, [%4];" : "=r"(v[i].x), "=r"(v[i].y), "=r"(v[i].z), "=r"(v[i].w) : "l"(src + i * 512) : "memory");
                    float e[4][4];
#pragma unroll
                    for (int i = 0; i < 4; i++) { e[i][0] = e[i][1] = e[i][2] = e[i][3] = 0.f; }
#pragma unroll
                    for (int i = 0; i < 8; i++) mma16(e[i & 3], v[i].x, v[i].y, v[i].z, v[i].w, sel0, sel1);
                    uint32_t bd[8];
#pragma unroll
                    for (int i = 0; i < 8; i++) bd[i] = or3(xor_or(v[i].x, v[i].y, tag), xor_or(v[i].z, v[i].w, tag), 0);
                    const bool bad = __any_sync(0xffffffffu, or3(or3(bd[0], bd[1], bd[2]), or3(bd[3], bd[4], bd[5]), or3(bd[6], bd[7], 0)) & 1);
                    const uint32_t p01 = pack2((e[0][0] + e[1][0]) + (e[2][0] + e[3][0]), (e[0][1] + e[1][1]) + (e[2][1] + e[3][1]));
                    const uint32_t p23 = pack2((e[0][2] + e[1][2]) + (e[2][2] + e[3][2]), (e[0][3] + e[1][3]) + (e[2][3] + e[3][3]));
                    const uint32_t x = __shfl_sync(0xffffffffu, p01, sl), y = __shfl_sync(0xffffffffu, p23, sl);
                    const uint32_t res = movm_t((tt & 1) ? y : x);
                    if (!bad) {
                        if (blk < 80) {
                            asm volatile("st.relaxed.gpu.global.u32 [%0], %1;" :: "l"(mdst), "r"(res) : "memory");
                            if (ln == 0) asm volatile("st.relaxed.gpu.global.u32 [%0], %1;" :: "l"(g_stamp + (s + 1) * 96 + oc), "r"(gtime()) : "memory");
                        }
                        PROFV(15, n);
                        break;
                    }
                    if (n > SPIN_LIMIT) __trap();
                }
                bar_arrive(9, 288);
                PROF(5); PROFG(26);
            } else if (w == 1) {
                const uint32_t now = gtime();
                int32_t a = -(1 << 30);
#pragma unroll
                for (int q = 0; q < 3; q++) {
                    const int32_t d = (int32_t)(__ldcg(g_stamp + s * 96 + (q * 32 + ln < 80 ? q * 32 + ln : ln)) - now);
                    if (d <= 0 && d > -100000) a = max(a, d);
                }
                a = __reduce_max_sync(0xffffffffu, a);
                const uint32_t an = now + a, ap = lds32(sm + C_PACE), pp = lds32(sm + C_PACE + 4);
                const uint32_t pn = s < 3 ? an - ap : (3 * pp + (an - ap)) >> 2;
                __syncwarp();
                if (ln == 0) {
                    asm volatile("st.shared.v4.u32 [%0], {%1,%2,%3,%3};" :: "r"(sm + C_PACE), "r"(an), "r"(pn), "r"(s < 3 || DG < -5000 ? 0u : (an + pn + DG) | 1u) : "memory");
                    mbar_expect(sm + CB_SC, 2560); mbar_expect(sm + CB_OX, 2048);
#pragma unroll
                    for (int c = 0; c < 4; c++) mbar_expect(sm + CB_MEM + 8 * c, j == 2 ? 2560 - 768 : 2560 - 896);
                }
                bar_arrive(10, 96);
                if (ln == 0) {
                    if (s + 3 < NSEG) asm volatile("prefetch.global.L2 [%0];" :: "l"(g_memg + (s + 3) * 2560 + oc * 32) : "memory");
                    if (s >= 4 * B_FINE + 1) flag_add(&g_flags.seg[(s - 1) * 32 + head], 2);
                    else if ((s & 3) == 0 && s > 0) flag_add(&g_flags.b[(s >> 2) - 1].qk, 2);
                }
                __syncwarp();
            } else {
                bar_sync(10, 96);
                const int nf = mem_forward(sm, s + 1, j, (w - 2) * 32 + ln, tw + D2, lds32(sm + C_PACE + 8));
                if (w == 2) { PROFV(20, nf); PROFG(29); }
            }
        }
    }
#define TPROF(i)
    __syncthreads();
    TPROF(0);
    constexpr int T_WG = 0, T_WU = 20480, T_WD = 40960, T_X = 65536, T_GU = 81920, T_RED = 106496, T_KEY = 122880;
    if (tid == 0) {
        mbar_expect(sm + CB_W, 40960 + (blk < 80 ? 24576 : 0));
        for (int c = 0; c < 5; c++) { tma2d(sm + T_WG + c * 4096, &mp.wgate, blk * 16, c * 128, sm + CB_W); tma2d(sm + T_WU + c * 4096, &mp.wup, blk * 16, c * 128, sm + CB_W); }
        if (blk < 80) for (int c = 0; c < 6; c++) tma2d(sm + T_WD + c * 4096, &mp.wdown, blk * 8, c * 256, sm + CB_W);
    }
    auto rkey = [](int idx) { uint32_t u = __ldcg((const unsigned short*)g_r + idx); u = (u & 0x8000u) ? (~u & 0xffffu) : (u | 0x8000u); return (u << 16) | (uint32_t)(S_TOK - 1 - idx); };
    if (warp < 8) {
        if (warp == 0 && lane == 0) for (int b = 0; b < 15; b++) flag_wait(&g_flags.b[b].ln, 128);
        bar_sync(1, 256);
        uint32_t k[8];
#pragma unroll
        for (int i = 0; i < 8; i++) { const int idx = warp * 240 + i * 32 + lane; k[i] = i * 32 + lane < 240 ? rkey(idx) : 0u; }
#pragma unroll 1
        for (int it = 0; it < 8; it++) {
            const uint32_t m = __reduce_max_sync(0xffffffffu, max(umax3(k[0], k[1], k[2]), max(umax3(k[3], k[4], k[5]), max(k[6], k[7]))));
#pragma unroll
            for (int i = 0; i < 8; i++) if (k[i] == m) k[i] = 0;
            if (lane == 0) asm volatile("st.shared.u32 [%0], %1;" :: "r"(sm + T_KEY + (warp * 8 + it) * 4), "r"(m) : "memory");
        }
    }
    __syncthreads();
    if (warp == 0) {
        uint32_t k[6];
        k[0] = lds32(sm + T_KEY + lane * 4); k[1] = lds32(sm + T_KEY + 128 + lane * 4);
        if (lane == 0) flag_wait(&g_flags.b[15].ln, 128);
        __syncwarp();
        TPROF(1);
#pragma unroll
        for (int i = 0; i < 4; i++) k[2 + i] = rkey(1920 + i * 32 + lane);
#pragma unroll 1
        for (int it = 0; it < 8; it++) {
            const uint32_t m = __reduce_max_sync(0xffffffffu, max(umax3(k[0], k[1], k[2]), umax3(k[3], k[4], k[5])));
#pragma unroll
            for (int i = 0; i < 6; i++) if (k[i] == m) k[i] = 0;
            if (lane == 0) asm volatile("st.shared.u32 [%0], %1;" :: "r"(sm + T_KEY + 256 + it * 4), "r"(S_TOK - 1 - (m & 0xffffu)) : "memory");
        }
    }
    __syncthreads();
    TPROF(2);
    for (int i = tid; i < 640; i += 384) {
        const uint4 v = __ldcg((const uint4*)(g_h2 + lds32(sm + T_KEY + 256 + (i & 7) * 4) * DM + (i >> 3) * 8));
        asm volatile("st.shared.v4.u32 [%0], {%1,%2,%3,%4};" :: "r"(sm + T_X + i * 16), "r"(v.x), "r"(v.y), "r"(v.z), "r"(v.w) : "memory");
    }
    const int trow = lds32(sm + T_KEY + 256 + (lane >> 2) * 4), tcol = (blk < 80 ? blk : 0) * 8 + (lane & 3) * 2;
    const uint32_t fx1 = __ldcg((const uint32_t*)(g_x1 + trow * DM + tcol)), fh2 = __ldcg((const uint32_t*)(g_h2 + trow * DM + tcol)),
                   fgb = __ldcg((const uint32_t*)(g_mod + 5 * DM + tcol));
    const float fr = __uint_as_float((uint32_t)__ldcg((const unsigned short*)g_r + trow) << 16);
    mbar_wait(sm + CB_W, 1);
    __syncthreads();
    TPROF(3);
    if (warp < 10) {
        float dg[4] = {0, 0, 0, 0}, du[4] = {0, 0, 0, 0};
#pragma unroll
        for (int k2 = 0; k2 < 2; k2++) {
            uint32_t b[4]; ldsm4(b, sm + T_X + (warp * 2 + k2) * 512 + lane * 16);
#pragma unroll
            for (int h = 0; h < 2; h++) {
                uint32_t ag[4], au[4];
                const uint32_t o = ((warp * 4 + k2 * 2 + h) * 16 + (mi >> 1) * 8 + r) * 32 + (mi & 1) * 16;
                ldsm4t(ag, sm + T_WG + o); ldsm4t(au, sm + T_WU + o);
                mma16(dg, ag[0], ag[1], ag[2], ag[3], b[2 * h], b[2 * h + 1]); mma16(du, au[0], au[1], au[2], au[3], b[2 * h], b[2 * h + 1]);
            }
        }
        sts128f(sm + T_RED + warp * 1024 + lane * 16, dg[0], dg[1], dg[2], dg[3]); sts128f(sm + T_RED + warp * 1024 + 512 + lane * 16, du[0], du[1], du[2], du[3]);
    }
    __syncthreads();
    if (warp == 0) {
        float g4[4] = {0, 0, 0, 0}, u4[4] = {0, 0, 0, 0};
#pragma unroll
        for (int i = 0; i < 10; i++) {
            const float4 a = lds128f(sm + T_RED + i * 1024 + lane * 16), b = lds128f(sm + T_RED + i * 1024 + 512 + lane * 16);
            g4[0] += a.x; g4[1] += a.y; g4[2] += a.z; g4[3] += a.w; u4[0] += b.x; u4[1] += b.y; u4[2] += b.z; u4[3] += b.w;
        }
        float y[4];
#pragma unroll
        for (int i = 0; i < 4; i++) { const float gq = bfr(g4[i]); y[i] = bfr(__fdividef(gq, 1.f + __expf(-gq))) * bfr(u4[i]); }
        g_gu[blk * 64 + lane] = movm_t(pack2(y[0], y[1])); g_gu[blk * 64 + 32 + lane] = movm_t(pack2(y[2], y[3]));
        __syncwarp();
        TPROF(4);
        if (lane == 0) {
            flag_add(&g_flags.gu);
            if (blk < 80) {
                flag_wait(&g_flags.gu, 96);
                mbar_expect(sm + CB_W2, 24576); bulk_g2s(sm + T_GU, g_gu, 24576, sm + CB_W2);
            }
        }
        __syncwarp();
    }
    if (blk < 80) {
        mbar_wait(sm + CB_W2, 1);
        TPROF(5);
        float d[4] = {0, 0, 0, 0};
#pragma unroll
        for (int k2 = 0; k2 < 4; k2++) {
            uint32_t b[4]; ldsm4t(b, sm + T_WD + (warp * 4 + k2) * 512 + lane * 16);
#pragma unroll
            for (int h = 0; h < 2; h++) {
                uint32_t a[4]; ldsm4(a, sm + T_GU + ((warp * 8 + k2 * 2 + h) * 2 + (mi >> 1)) * 128 + r * 16);
                mma16(d, a[0], a[1], a[2], a[3], b[2 * h], b[2 * h + 1]);
            }
        }
        asm volatile("st.shared.v2.f32 [%0], {%1,%2};" :: "r"(sm + T_RED + warp * 256 + lane * 8), "f"(d[0]), "f"(d[1]) : "memory");
        __syncthreads();
        if (warp == 0) {
            float y0 = 0, y1 = 0;
#pragma unroll
            for (int i = 0; i < 12; i++) { const float2 a = lds64f(sm + T_RED + i * 256 + lane * 8); y0 += a.x; y1 += a.y; }
            const float sg = bfr(__fdividef(1.f, 1.f + __expf(-fr)));
            const float b0 = bfr(lo_f(fh2) + bfr(bfr(y0) * sg)), b1 = bfr(hi_f(fh2) + bfr(bfr(y1) * sg));
            *(uint32_t*)(ar.out + trow * DM + tcol) = pack2(lo_f(fx1) + bfr(lo_f(fgb) * b0), hi_f(fx1) + bfr(hi_f(fgb) * b1));
        }
    }
    TPROF(6);
    if (tid == 0) flags_release();
}

struct SideMaps { CUtensorMap h, wv, vst, q32, k32, v32, km, vm, ost, o, wo, slab3, slab2; };
constexpr int SD_ST = 43008, SD_NST = 4, SD_EPI = SD_NST * SD_ST, SD_LN = SD_EPI + 2 * 24576, SD_BAR = SD_LN + 10240, SD_SMEM = SD_BAR + 256;
#define N_ATT 10
__device__ __forceinline__ int o_split(int b) { return b >= B_FINE ? 16 : 8; }
__device__ __forceinline__ int next_item(bool att, int (&cur)[4], int& fix) {
    for (int n = 0;; n++) {
        if (!att) { cur[1] = max(cur[1], cur[2]); cur[3] = max(cur[3], cur[2] - SLABS); }
        if (cur[3] >= B_FINE && (att || cur[0] > 15)) {
            const int b = fix >> 2, c = blockIdx.x;
            if (c >= 32 || b == 16) return -1;
            if ((fix & 3) == 0) { fix++; return 1 << 16 | b << 8 | c; }
            if ((fix & 3) == 1) { fix++; return 2 << 16 | b << 8 | c; }
            if ((fix & 3) == 3) { fix -= 2; return 3 << 16 | (b - 1) << 8 | c; }
            if (b == 14 || (b < 14 && ld_rlx(&g_flags.seg[(4 * b + 6) * 32 + c]) >= 6)) { fix += 5; return 1 << 16 | (b + 1) << 8 | c; }
            fix += 2; return 3 << 16 | b << 8 | c;
        }
        uint32_t f3, c3, f2, c2, f1, f1v, c1; [[maybe_unused]] uint32_t dummy;
        asm volatile("ld.relaxed.gpu.global.v2.u32 {%0,%1}, [%2];" : "=r"(f3), "=r"(c3) : "l"(&g_flags.b[cur[3] & 15].o) : "memory");
        asm volatile("ld.relaxed.gpu.global.v2.u32 {%0,%1}, [%2];" : "=r"(f2), "=r"(c2) : "l"(&g_flags.b[cur[2] & 15].at) : "memory");
        asm volatile("ld.relaxed.gpu.global.v4.u32 {%0,%1,%2,%3}, [%4];" : "=r"(f1), "=r"(f1v), "=r"(c1), "=r"(dummy) : "l"(&g_flags.b[cur[1] & 15].qk) : "memory");
        const uint32_t f2l = ld_rlx(&g_flags.b[(cur[2] - SLABS) & 15].ln);
        const bool e3 = cur[3] < B_FINE && c3 >= 2u * o_split(cur[3]), e2 = cur[2] < B_FINE && c2 >= 2u * o_split(cur[2]), e1 = cur[1] < B_FINE && c1 >= 32;
        const bool r3 = !e3 && cur[3] < B_FINE && f3 >= 4u * o_split(cur[3]), r2 = !e2 && cur[2] < B_FINE && f2 >= 64 && (cur[2] < SLABS || f2l >= 128),
                   r1 = !e1 && cur[1] < B_FINE && f1 >= 192 && f1v >= 64, r0 = cur[0] < 16;
        const int kind = att ? (r3 ? 3 : r2 ? 2 : r1 ? 1 : (cur[1] == 0 && r0) ? 0 : -1)
                             : r0 ? ((cur[0] > cur[2] + 3 && r2) ? 2 : 0) : (r3 ? 3 : r2 ? 2 : r1 ? 1 : -1);
        const int b = kind == 3 ? cur[3] : kind == 2 ? cur[2] : kind == 1 ? cur[1] : cur[0];
        cur[3] += e3; cur[2] += e2; cur[1] += e1;
        if (kind < 0) { if (n > (1 << 22)) __trap(); continue; }
        uint32_t i; asm volatile("atom.relaxed.gpu.global.add.u32 %0, [%1], 1;" : "=r"(i)
            : "l"(kind == 3 ? &g_flags.b[b].c3 : kind == 2 ? &g_flags.b[b].c2 : kind == 1 ? &g_flags.b[b].c1 : &g_flags.b[b].c0) : "memory");
        if (i < (kind < 2 ? 32u : 2u * o_split(b))) {
            return kind << 16 | b << 8 | i;
        }
        if (kind == 0) cur[0]++;
    }
}

template <int NP>
__device__ __forceinline__ void tile_out(const float (&acc)[8 * NP], uint32_t eb, uint32_t efull, uint32_t eempty, int& eph, int w, int lane) {
    const int r = lane & 7, mi = lane >> 3, row = w * 16 + (mi & 1) * 8 + r;
    mbar_wait(eempty, eph); eph ^= 1;
#pragma unroll
    for (int p = 0; p < NP; p++) {
        const int oc = 2 * p + (mi >> 1);
        stsm4(eb + (oc >> 3) * 8192 + row * 128 + (((oc & 7) ^ r) << 4), pack2(acc[8 * p], acc[8 * p + 1]), pack2(acc[8 * p + 2], acc[8 * p + 3]),
              pack2(acc[8 * p + 4], acc[8 * p + 5]), pack2(acc[8 * p + 6], acc[8 * p + 7]));
    }
    asm volatile("fence.proxy.async.shared::cta;" ::: "memory");
    __syncwarp();
    if (lane == 0) mbar_arrive(efull);
}

template <int MT>
__device__ __forceinline__ void attn_tile(uint32_t base, uint32_t dst, uint32_t eempty, int eph, int lane) {
    constexpr int NK = MT ? 5 : 3;
    const int r = lane & 7, mi = lane >> 3, g = lane >> 2, t = lane & 3;
    float sc[NK][4];
#pragma unroll
    for (int n = 0; n < NK; n++) sc[n][0] = sc[n][1] = sc[n][2] = sc[n][3] = 0.f;
#pragma unroll 1
    for (int k2 = 0; k2 < 6; k2++) {
        const uint32_t cb = (k2 >> 1) * 4096, c0 = (k2 & 1) * 4;
        uint32_t a0[4], a1[4], bb[NK][4];
        ldsm4(a0, base + cb + (16 * MT + (mi & 1) * 8 + r) * 128 + (((c0 + (mi >> 1)) ^ r) << 4));
        ldsm4(a1, base + cb + (16 * MT + (mi & 1) * 8 + r) * 128 + (((c0 + 2 + (mi >> 1)) ^ r) << 4));
#pragma unroll
        for (int n = 0; n < NK; n++)
            ldsm4(bb[n], (n < NK - 1 ? base + 12288 + cb + (8 * n + r) * 128 : base + 36864 + (k2 >> 1) * 1024 + r * 128) + (((c0 + mi) ^ r) << 4));
#pragma unroll
        for (int n = 0; n < NK; n++) mma16(sc[n], a0[0], a0[1], a0[2], a0[3], bb[n][0], bb[n][1]);
#pragma unroll
        for (int n = 0; n < NK; n++) mma16(sc[n], a1[0], a1[1], a1[2], a1[3], bb[n][2], bb[n][3]);
    }
    const float scale = 0.07216878364870322f, l2e = 1.4426950408889634f;
    float v[2][2 * NK], mx[2], sum[2];
#pragma unroll
    for (int hf = 0; hf < 2; hf++) {
        mx[hf] = -INFINITY;
#pragma unroll
        for (int n = 0; n < NK; n++) {
            uint32_t u = pack2(sc[n][2 * hf], sc[n][2 * hf + 1]);
            u = pack2(lo_f(u) * scale, hi_f(u) * scale);
            const int lim = 16 * MT + 8 * hf + g - 8 * n - 2 * t;
            v[hf][2 * n] = (n < NK - 1 && lim < 0) ? -1e9f : lo_f(u);
            v[hf][2 * n + 1] = (n < NK - 1 && lim < 1) ? -1e9f : hi_f(u);
            mx[hf] = fmaxf(mx[hf], fmaxf(v[hf][2 * n], v[hf][2 * n + 1]));
        }
    }
#pragma unroll
    for (int o = 1; o < 4; o <<= 1)
#pragma unroll
        for (int hf = 0; hf < 2; hf++) mx[hf] = fmaxf(mx[hf], __shfl_xor_sync(0xffffffffu, mx[hf], o));
#pragma unroll
    for (int hf = 0; hf < 2; hf++) {
        sum[hf] = 0;
#pragma unroll
        for (int q = 0; q < 2 * NK; q++) { asm("ex2.approx.ftz.f32 %0, %1;" : "=f"(v[hf][q]) : "f"((v[hf][q] - mx[hf]) * l2e)); sum[hf] += v[hf][q]; }
    }
#pragma unroll
    for (int o = 1; o < 4; o <<= 1)
#pragma unroll
        for (int hf = 0; hf < 2; hf++) sum[hf] += __shfl_xor_sync(0xffffffffu, sum[hf], o);
    uint32_t pa[NK][2];
#pragma unroll
    for (int hf = 0; hf < 2; hf++) {
        const float inv = __fdividef(1.f, sum[hf]);
#pragma unroll
        for (int n = 0; n < NK; n++) pa[n][hf] = pack2(v[hf][2 * n] * inv, v[hf][2 * n + 1] * inv);
    }
    mbar_wait(eempty, eph);
#pragma unroll 1
    for (int n4 = 0; n4 < 6; n4++) {
        const uint32_t cb = (n4 >> 1) * 4096, c0 = (n4 & 1) * 4;
        uint32_t bm[4], bb[4][4];
        ldsm4t(bm, base + 39936 + (n4 >> 1) * 1024 + r * 128 + (((c0 + mi) ^ r) << 4));
#pragma unroll
        for (int u = 0; u < 4; u++) ldsm4t(bb[u], base + 24576 + cb + (8 * mi + r) * 128 + (((c0 + u) ^ r) << 4));
        float o[4][4];
#pragma unroll
        for (int u = 0; u < 4; u++) { o[u][0] = o[u][1] = o[u][2] = o[u][3] = 0.f; mma8(o[u], pa[NK - 1][0], pa[NK - 1][1], bm[u]); }
#pragma unroll
        for (int u = 0; u < 4; u++) mma16(o[u], pa[0][0], pa[0][1], pa[1][0], pa[1][1], bb[u][0], bb[u][1]);
        if (MT) {
#pragma unroll
            for (int u = 0; u < 4; u++) mma16(o[u], pa[MT ? 2 : 0][0], pa[MT ? 2 : 0][1], pa[MT ? 3 : 0][0], pa[MT ? 3 : 0][1], bb[u][2], bb[u][3]);
        }
#pragma unroll
        for (int p = 0; p < 2; p++)
            stsm4(dst + (n4 >> 1) * 8192 + ((mi & 1) * 8 + r) * 128 + (((c0 + 2 * p + (mi >> 1)) ^ r) << 4), pack2(o[2 * p][0], o[2 * p][1]), pack2(o[2 * p][2], o[2 * p][3]),
                  pack2(o[2 * p + 1][0], o[2 * p + 1][1]), pack2(o[2 * p + 1][2], o[2 * p + 1][3]));
    }
}

__global__ void __launch_bounds__(384, 1) k_side(const __grid_constant__ SideMaps mp, const bf16* __restrict__ x, const bf16* __restrict__ wr,
                                                 bf16* __restrict__ out) {
    extern __shared__ __align__(1024) uint8_t smraw[];
    const uint32_t sm = smem_u32(smraw);
    if (sm & 1023) __trap();
    const uint32_t FULL = sm + SD_BAR, EMPTY = FULL + 32, EFULL = FULL + 64, EEMPTY = FULL + 80, IFULL = FULL + 96, IEMPTY = FULL + 128, IQ = FULL + 160, SCHED = FULL + 176, LNDONE = FULL + 184;
    const int tid = threadIdx.x, warp = __shfl_sync(0xffffffffu, tid >> 5, 0), lane = tid & 31;
    const uint64_t ef = policy_stream();
    if (tid == 0) {
        for (int i = 0; i < SD_NST; i++) { mbar_init(FULL + 8 * i, 1); mbar_init(EMPTY + 8 * i, 2); }
        for (int i = 0; i < 2; i++) { mbar_init(EFULL + 8 * i, 4); mbar_init(EEMPTY + 8 * i, 1); }
        for (int i = 0; i < 4; i++) { mbar_init(IFULL + 8 * i, 1); mbar_init(IEMPTY + 8 * i, 11); }
        mbar_init(SCHED, 1); mbar_init(LNDONE, 1);
        asm volatile("fence.mbarrier_init.release.cluster;" ::: "memory");
    }
    __syncthreads();
    if (warp >= 8) {
      asm volatile("setmaxnreg.dec.sync.aligned.u32 40;");
      if (warp == 8) {
        int st = 0, ph = 1;
        for (int q = 0;; q++) {
            mbar_wait(IFULL + 8 * (q & 3), (q >> 2) & 1);
            const int it = __shfl_sync(0xffffffffu, lds32(IQ + 4 * (q & 3)), 0);
            if (elect()) mbar_arrive(IEMPTY + 8 * (q & 3));
            if (it < 0) break;
            const int kind = it >> 16, b = (it >> 8) & 255, i = it & 255;
            if (kind == 3) { if (elect()) mbar_arrive(SCHED); continue; }
            const int nst = kind == 0 ? 10 : kind == 1 ? 4 : 192 / o_split(b);
            const int ksched = kind == 0 ? 4 : kind == 2 ? nst - (b < B_FINE ? 7 : 4) : 0;
            if (kind == 1 && b >= B_FINE) flag_wait(&g_flags.v[b * 32 + i], 2);
            for (int kb = 0; kb < nst; kb++) {
                mbar_wait(EMPTY + 8 * st, ph);
                const uint32_t base = sm + st * SD_ST, fb = FULL + 8 * st;
                if (kb == ksched && elect()) mbar_arrive(SCHED);
                if (kind == 0) {
                    if (elect()) {
                        mbar_expect(fb, 40960);
                        tma2d(base, &mp.h, kb * 64, b * 128, fb);
                        tma3d(base + 16384, &mp.wv, kb * 64, i * 3, fb);
                    }
                } else if (kind == 1) {
                    if (b >= B_FINE) flag_wait(&g_flags.seg[(b * 4 + kb) * 32 + i], 6);
                    if (elect()) {
                        mbar_expect(fb, 43008);
                        const int row = b * 128 + kb * 32, mrow = ((b * 4 + kb) * NH + i) * 8;
                        tma3d_ef(base, &mp.q32, row, i * 3, fb, ef);
                        tma3d_ef(base + 12288, &mp.k32, row, i * 3, fb, ef);
                        tma3d_ef(base + 36864, &mp.km, mrow, 0, fb, ef);
                        tma3d_ef(base + 24576, &mp.v32, row, i * 3, fb, ef);
                        tma3d_ef(base + 39936, &mp.vm, mrow, 0, fb, ef);
                    }
                } else {
                    const int k0 = ((i >> 1) * nst + kb) * 32;
                    if (elect()) { mbar_expect(fb, 28672); tma3d(base + 8192, &mp.wo, k0, (i & 1) * 5, fb); }
                    if (kb == 0 && b >= B_FINE) flag_wait(&g_flags.pair[b * 16 + (i >> 1)], 4);
                    if (elect()) tma2d_ef(base, &mp.o, k0, b * 128, fb, ef);
                }
                __syncwarp();
                if (++st == SD_NST) { st = 0; ph ^= 1; }
            }
        }
      } else if (warp == 11) {
        if (lane == 0) {
            int cur[4] = {0, 0, blockIdx.x < N_ATT ? B_FINE : 0, 0}, fix = 4 * B_FINE;
            flag_wait(&g_flags.h, 160);
            for (int q = 0;; q++) {
                if (q) mbar_wait(SCHED, (q - 1) & 1);
                const int it = next_item(blockIdx.x < N_ATT, cur, fix);
                if (it >> 16 == 3 && ((it >> 8) & 255) >= B_FINE) flag_wait(&g_flags.b[(it >> 8) & 255].o, 64);
                if (it >> 16 == 1)
                    asm volatile("cp.async.bulk.prefetch.L2.global [%0], 5120;" :: "l"(x + (((it >> 8) & 255) * 128 + (it & 31) * 4) * DM) : "memory");
                mbar_wait(IEMPTY + 8 * (q & 3), ((q >> 2) & 1) ^ 1);
                asm volatile("st.shared.u32 [%0], %1;" :: "r"(IQ + 4 * (q & 3)), "r"(it) : "memory");
                mbar_arrive(IFULL + 8 * (q & 3));
                if (it < 0) { flags_release(); break; }
            }
        }
      } else {
        if (lane == 0) {
            const int wg = warp - 9; int ph = 0, lph = 0;
            for (int q = 0;; q++) {
                mbar_wait(IFULL + 8 * (q & 3), (q >> 2) & 1);
                const int it = lds32(IQ + 4 * (q & 3));
                mbar_arrive(IEMPTY + 8 * (q & 3));
                if (it < 0) break;
                const int kind = it >> 16, b = (it >> 8) & 255, i = it & 255;
                if (kind > 2) {
                    if (wg == 0) { mbar_wait(LNDONE, lph); lph ^= 1; flag_add(&g_flags.b[b].ln, 64 / o_split(b)); }
                    continue;
                }
                if (kind == 2 && b >= B_FINE) { flag_wait(&g_flags.b[b - SLABS].ln, 128); }
                for (int rd = 0; rd < (kind == 2 ? 2 : 1); rd++) {
                    mbar_wait(EFULL + 8 * wg, ph); ph ^= 1;
                    const uint32_t src = sm + SD_EPI + wg * 24576;
                    if (kind == 2) tma3d_store(rd ? &mp.slab2 : &mp.slab3, ((b % SLABS) * KSPLIT + (i >> 1)) * 128 + wg * 64, (i & 1) * 5 + rd * 3, src, ef, false);
                    else tma3d_store(kind == 0 ? &mp.vst : &mp.ost, b * 128 + wg * 64, i * 3, src, ef, kind == 0 && b > 1);
                    asm volatile("cp.async.bulk.commit_group;" ::: "memory");
                    asm volatile("cp.async.bulk.wait_group.read 0;" ::: "memory");
                    mbar_arrive(EEMPTY + 8 * wg);
                }
                asm volatile("cp.async.bulk.wait_group 0;" ::: "memory");
                bump(kind == 0 ? &g_flags.v[b * 32 + i] : kind == 1 ? (b >= B_FINE ? &g_flags.pair[b * 16 + (i >> 1)] : &g_flags.b[b].at) : &g_flags.b[b].o);
                if (kind == 0) bump(&g_flags.b[b].vb);
            }
        }
      }
    } else {
        asm volatile("setmaxnreg.inc.sync.aligned.u32 232;");
        const int wg = warp >> 2, w = warp & 3;
        int st = 0, ph = 0, eph = 1;
        const uint32_t eb = sm + SD_EPI + wg * 24576;
        for (int q = 0;; q++) {
            mbar_wait(IFULL + 8 * (q & 3), (q >> 2) & 1);
            const int itc = lds32(IQ + 4 * (q & 3));
            __syncwarp();
            if (lane == 0) mbar_arrive(IEMPTY + 8 * (q & 3));
            if (itc < 0) break;
            const int kind = itc >> 16, b = (itc >> 8) & 255, i = itc & 255;
            if (kind == 0) {
                float acc[96];
#pragma unroll
                for (int n = 0; n < 96; n++) acc[n] = 0.f;
                int prev = -1;
                for (int kb = 0; kb < 10; kb++) {
                    mbar_wait(FULL + 8 * st, ph);
                    const uint32_t base = sm + st * SD_ST;
                    WG_FENCE();
#pragma unroll
                    for (int ks = 0; ks < 4; ks++)
                        wgmma_ss_n192_tb(acc, mkdesc(base + wg * 8192 + ks * 32, 16, 1024), mkdesc(base + 16384 + ks * 2048, 8192, 1024), (kb | ks) != 0);
                    WG_COMMIT();
                    if (prev >= 0) { WG_WAIT(1); if ((tid & 127) == 0) mbar_arrive(EMPTY + 8 * prev); }
                    prev = st;
                    if (++st == SD_NST) { st = 0; ph ^= 1; }
                }
                WG_WAIT(0);
                if ((tid & 127) == 0) mbar_arrive(EMPTY + 8 * prev);
                tile_out<12>(acc, eb, EFULL + 8 * wg, EEMPTY + 8 * wg, eph, w, lane);
            } else if (kind == 1) {
                const int seg = warp >> 1, mt = warp & 1;
                int sst = st + seg, sph = ph; if (sst >= SD_NST) { sst -= SD_NST; sph ^= 1; }
                ph ^= 1;
                mbar_wait(FULL + 8 * sst, sph);
                const uint32_t base = sm + sst * SD_ST;
                if (mt) attn_tile<1>(base, eb + (w * 16) * 128, EEMPTY + 8 * wg, eph, lane);
                else attn_tile<0>(base, eb + (w * 16) * 128, EEMPTY + 8 * wg, eph, lane);
                eph ^= 1;
                asm volatile("fence.proxy.async.shared::cta;" ::: "memory");
                __syncwarp();
                if (lane == 0) { mbar_arrive(EMPTY + 8 * sst); mbar_arrive(EFULL + 8 * wg); }
            } else if (kind == 2) {
                float acc[96], acc2[64];
#pragma unroll
                for (int n = 0; n < 96; n++) acc[n] = 0.f;
#pragma unroll
                for (int n = 0; n < 64; n++) acc2[n] = 0.f;
                int prev = -1;
                for (int kb = 192 / o_split(b); kb > 0; kb--) {
                    const uint32_t base = sm + st * SD_ST;
                    mbar_wait(FULL + 8 * st, ph);
                    WG_FENCE();
#pragma unroll
                    for (int ks = 0; ks < 2; ks++) {
                        const uint64_t da = (mkdesc(base + wg * 4096 + ks * 32, 16, 512) & ~(3ull << 62)) | (2ull << 62);
                        wgmma_ss_n192_tb(acc, da, mkdesc(base + 8192 + ks * 2048, 4096, 1024), 1);
                        wgmma_ss_n128_tb(acc2, da, mkdesc(base + 8192 + 3 * 4096 + ks * 2048, 4096, 1024), 1);
                    }
                    WG_COMMIT();
                    if (prev >= 0) { WG_WAIT(1); if ((tid & 127) == 0) mbar_arrive(EMPTY + 8 * prev); }
                    prev = st;
                    if (++st == SD_NST) { st = 0; ph ^= 1; }
                }
                WG_WAIT(0);
                if ((tid & 127) == 0) mbar_arrive(EMPTY + 8 * prev);
                tile_out<12>(acc, eb, EFULL + 8 * wg, EEMPTY + 8 * wg, eph, w, lane);
                tile_out<8>(acc2, eb, EFULL + 8 * wg, EEMPTY + 8 * wg, eph, w, lane);
            } else {
                const bool two = o_split(b) == 16;
                const int lrow = two ? i * 4 + w : i * 8 + warp, row = b * 128 + lrow;
                const bf16* sl = g_slab + ((size_t)((b % SLABS) * KSPLIT + (two ? wg * 8 : 0)) * 128 + lrow) * DM + lane * 4;
                uint2 ga[5], gb[5], sh[5], sc[5], wv[5], xin[5];
                float xv[20], hv[20];
                {
#pragma unroll
                    for (int q2 = 0; q2 < 5; q2++) {
                        const int c = lane * 4 + q2 * 128;
                        ga[q2] = __ldcg((const uint2*)(g_mod + 2 * DM + c)); sh[q2] = __ldcg((const uint2*)(g_mod + 3 * DM + c));
                        sc[q2] = __ldcg((const uint2*)(g_mod + 4 * DM + c)); gb[q2] = __ldcg((const uint2*)(g_mod + 5 * DM + c));
                        wv[q2] = __ldg((const uint2*)(wr + c)); xin[q2] = ld_ef(x + row * DM + c, ef);
                    }
                }
                {
                    uint2 z[5][8];
#pragma unroll
                    for (int q2 = 0; q2 < 5; q2++)
#pragma unroll
                        for (int k = 0; k < 8; k++) z[q2][k] = ld_ef(sl + (size_t)k * 128 * DM + q2 * 128, ef);
#pragma unroll
                    for (int q2 = 0; q2 < 5; q2++) {
                        xv[4 * q2] = xv[4 * q2 + 1] = xv[4 * q2 + 2] = xv[4 * q2 + 3] = 0.f;
#pragma unroll
                        for (int k = 0; k < 8; k++) { xv[4 * q2] += lo_f(z[q2][k].x); xv[4 * q2 + 1] += hi_f(z[q2][k].x); xv[4 * q2 + 2] += lo_f(z[q2][k].y); xv[4 * q2 + 3] += hi_f(z[q2][k].y); }
                    }
                }
                if (two) {
                    const uint32_t xb = sm + SD_LN + w * 2560 + lane * 16;
                    if (wg == 1) {
#pragma unroll
                        for (int q2 = 0; q2 < 5; q2++) sts128f(xb + q2 * 512, xv[4 * q2], xv[4 * q2 + 1], xv[4 * q2 + 2], xv[4 * q2 + 3]);
                        bar_arrive(2, 256);
                        continue;
                    }
                    bar_sync(2, 256);
#pragma unroll
                    for (int q2 = 0; q2 < 5; q2++) { const float4 z = lds128f(xb + q2 * 512); xv[4 * q2] += z.x; xv[4 * q2 + 1] += z.y; xv[4 * q2 + 2] += z.z; xv[4 * q2 + 3] += z.w; }
                }
                uint32_t sv[10], tv[10];
#pragma unroll
                for (int q2 = 0; q2 < 10; q2++) {
                    const uint32_t xi = q2 & 1 ? xin[q2 >> 1].y : xin[q2 >> 1].x, gi = q2 & 1 ? ga[q2 >> 1].y : ga[q2 >> 1].x;
                    xv[2 * q2] = bfr(lo_f(xi) + bfr(lo_f(gi) * bfr(xv[2 * q2]))); xv[2 * q2 + 1] = bfr(hi_f(xi) + bfr(hi_f(gi) * bfr(xv[2 * q2 + 1])));
                    sv[q2] = q2 & 1 ? sc[q2 >> 1].y : sc[q2 >> 1].x; tv[q2] = q2 & 1 ? sh[q2 >> 1].y : sh[q2 >> 1].x;
                }
                ln_mod(xv, sv, tv, hv);
                float rs = 0;
#pragma unroll
                for (int q2 = 0; q2 < 5; q2++) {
                    const int c = row * DM + lane * 4 + q2 * 128;
                    const float* xx = xv + 4 * q2; const float* hh = hv + 4 * q2;
                    rs += (hh[0] * lo_f(wv[q2].x) + hh[1] * hi_f(wv[q2].x)) + (hh[2] * lo_f(wv[q2].y) + hh[3] * hi_f(wv[q2].y));
                    st_ef(g_x1 + c, make_uint2(pack2(xx[0], xx[1]), pack2(xx[2], xx[3])), ef);
                    st_ef(g_h2 + c, make_uint2(pack2(hh[0], hh[1]), pack2(hh[2], hh[3])), ef);
                    st_ef(out + c, make_uint2(pack2(xx[0] + bfr(lo_f(gb[q2].x) * hh[0]), xx[1] + bfr(hi_f(gb[q2].x) * hh[1])),
                                              pack2(xx[2] + bfr(lo_f(gb[q2].y) * hh[2]), xx[3] + bfr(hi_f(gb[q2].y) * hh[3]))), ef);
                }
                rs = warp_sum(rs);
                if (lane == 0) g_r[row] = __float2bfloat16_rn(rs);
                bar_sync(1, two ? 128 : 256);
                if (tid == 0) mbar_arrive(LNDONE);
            }
        }
    }
    __syncwarp();
    asm volatile("griddepcontrol.wait;" ::: "memory");
}

#define P_D1 400
#define P_DL 700
#define P_DG 0
typedef CUresult (*EncodeFn)(CUtensorMap*, CUtensorMapDataType, cuuint32_t, void*, const cuuint64_t*, const cuuint64_t*, const cuuint32_t*, const cuuint32_t*,
                             CUtensorMapInterleave, CUtensorMapSwizzle, CUtensorMapL2promotion, CUtensorMapFloatOOBfill);
static EncodeFn s_encode = nullptr;
static void make_map(CUtensorMap* m, const void* p, int rows, int cols, int box_rows, int box_cols = 64) {
    cuuint64_t dims[2] = {(cuuint64_t)cols, (cuuint64_t)rows}, strides[1] = {(cuuint64_t)cols * 2};
    cuuint32_t box[2] = {(cuuint32_t)box_cols, (cuuint32_t)box_rows}, es[2] = {1, 1};
    s_encode(m, CU_TENSOR_MAP_DATA_TYPE_BFLOAT16, 2, (void*)p, dims, strides, box, es, CU_TENSOR_MAP_INTERLEAVE_NONE,
             box_cols == 64 ? CU_TENSOR_MAP_SWIZZLE_128B : box_cols == 32 ? CU_TENSOR_MAP_SWIZZLE_64B : CU_TENSOR_MAP_SWIZZLE_NONE, CU_TENSOR_MAP_L2_PROMOTION_L2_256B, CU_TENSOR_MAP_FLOAT_OOB_FILL_NONE);
}
static void make_map3(CUtensorMap* m, const void* p, int rows, int cols, int box_rows, int box_chunks) {
    cuuint64_t dims[3] = {64, (cuuint64_t)rows, (cuuint64_t)cols / 64}, strides[2] = {(cuuint64_t)cols * 2, 128};
    cuuint32_t box[3] = {64, (cuuint32_t)box_rows, (cuuint32_t)box_chunks}, es[3] = {1, 1, 1};
    s_encode(m, CU_TENSOR_MAP_DATA_TYPE_BFLOAT16, 3, (void*)p, dims, strides, box, es, CU_TENSOR_MAP_INTERLEAVE_NONE,
             CU_TENSOR_MAP_SWIZZLE_128B, CU_TENSOR_MAP_L2_PROMOTION_L2_256B, CU_TENSOR_MAP_FLOAT_OOB_FILL_NONE);
}
template <typename T> static void* sym(T& s) { void* p = nullptr; cudaGetSymbolAddress(&p, s); return p; }

extern "C" void kernel_launch(void* const* d_in, const int* in_sizes, int n_in, void* d_out, int out_size) {
    const bf16 *x = (const bf16*)d_in[0], *mem0 = (const bf16*)d_in[1], *Wq = (const bf16*)d_in[2], *Wk = (const bf16*)d_in[3],
               *Wv = (const bf16*)d_in[4], *Wo = (const bf16*)d_in[5], *wr = (const bf16*)d_in[8], *wgate = (const bf16*)d_in[9],
               *wup = (const bf16*)d_in[10], *wdown = (const bf16*)d_in[11], *c = (const bf16*)d_in[12], *wmod = (const bf16*)d_in[13];
    bf16* out = (bf16*)d_out;
    if (!s_encode) {
        cudaDriverEntryPointQueryResult qr;
        cudaGetDriverEntryPoint("cuTensorMapEncodeTiled", (void**)&s_encode, cudaEnableDefault, &qr);
        cudaFuncSetAttribute(k_side, cudaFuncAttributeMaxDynamicSharedMemorySize, SD_SMEM);
        cudaFuncSetAttribute(k_chain, cudaFuncAttributeMaxDynamicSharedMemorySize, C_SMEM);
    }
    ChainMaps cm; SideMaps sd;
    make_map(&sd.h, sym(g_h), S_TOK, DM, 128); make_map3(&sd.wv, Wv, DM, HD, 64, 3); make_map3(&sd.vst, sym(g_v), S_TOK, HD, 64, 3);
    make_map3(&sd.q32, sym(g_q), S_TOK, HD, 32, 3); make_map3(&sd.k32, sym(g_k), S_TOK, HD, 32, 3); make_map3(&sd.v32, sym(g_v), S_TOK, HD, 32, 3);
    make_map3(&sd.km, sym(g_km), NSEG * NH * 8, DH, 8, 3); make_map3(&sd.vm, sym(g_vm), NSEG * NH * 8, DH, 8, 3);
    make_map3(&sd.ost, sym(g_o), S_TOK, HD, 64, 3); make_map(&sd.o, sym(g_o), S_TOK, HD, 128, 32); make_map3(&sd.wo, Wo, HD, DM, 32, 5);
    make_map3(&sd.slab3, sym(g_slab), SLABS * KSPLIT * 128, DM, 64, 3); make_map3(&sd.slab2, sym(g_slab), SLABS * KSPLIT * 128, DM, 64, 2);
    make_map(&cm.wq, Wq, DM, HD, 64); make_map(&cm.wk, Wk, DM, HD, 64); make_map(&cm.wv, Wv, DM, HD, 64); make_map(&cm.wo, Wo, HD, DM, 192, 32);
    make_map(&cm.h32, sym(g_h), S_TOK, DM, 32);
    make_map(&cm.q32, sym(g_q), S_TOK, HD, 32); make_map(&cm.k32, sym(g_k), S_TOK, HD, 32); make_map(&cm.v32, sym(g_v), S_TOK, HD, 32);
    make_map(&cm.wgate, wgate, DM, FF, 128, 16); make_map(&cm.wup, wup, DM, FF, 128, 16); make_map(&cm.wdown, wdown, FF, DM, 256, 8);
    make_map(&cm.wmod, wmod, DM, 6 * DM, 160, 48);
    ChainArgs ar = {x, mem0, c, Wv, Wo, out, P_D1, P_DL, P_DG};
    k_chain<<<96, 384, C_SMEM>>>(cm, ar);
    cudaLaunchConfig_t cfg = {};
    cfg.gridDim = dim3(N_SIDE); cfg.blockDim = dim3(384); cfg.dynamicSmemBytes = SD_SMEM; cfg.stream = cudaStreamPerThread;
    cudaLaunchAttribute at[1]; at[0].id = cudaLaunchAttributeProgrammaticStreamSerialization; at[0].val.programmaticStreamSerializationAllowed = 1;
    cfg.attrs = at; cfg.numAttrs = 1;
    cudaLaunchKernelEx(&cfg, k_side, sd, x, wr, out);
}
```

```cpp
#include <cuda_runtime.h>
#include <cuda_bf16.h>
#include <cuda.h>
#include <stdint.h>
#include <stdio.h>
#include <string.h>
#include <stdlib.h>

typedef __nv_bfloat16 bf16;
constexpr int S_TOK = 2048, DM = 640, NH = 32, DH = 192, HD = NH * DH, NSEG = 64, SEG = 32, FF = 1536;

__device__ bf16 g_mod[6 * DM];
__device__ bf16 g_h[S_TOK * DM];
constexpr int REC = 43008, R_Q = 12288, R_K = R_Q + 4096, R_KM = R_Q + 8192, R_VM = R_Q + 9216, R_J = 10240;
__device__ __align__(1024) uint8_t g_rec[(size_t)NSEG * NH * REC];
__host__ __device__ constexpr uint32_t vswz(uint32_t t) { return (t ^ (t >> 3 << 1)) & 7; }
__device__ bf16 g_o[S_TOK * HD];
__device__ bf16 g_x1[S_TOK * DM];
__device__ bf16 g_h2[S_TOK * DM];
__device__ bf16 g_r[S_TOK];
__device__ __align__(128) uint32_t g_gu[FF / 8 * 32];
__device__ __align__(1024) uint8_t g_acc[32 * 32768];
__device__ float g_slow[2 * NH * 20 * 32 * 8];
constexpr int NSLAB = 160;
__device__ bf16 g_slab[NSLAB * 128 * DM];
struct __align__(128) Flags {
    uint32_t v[16 * 32];
    uint32_t seg[64 * 32];
    uint32_t at[16 * 32];
    uint32_t o[16 * 32];
    uint32_t ln[16 * 32];
    uint32_t gu, pad1[31], next, pad2[31], slow, pad3[31];
    uint32_t mod, h, pad4[30], done, pad5[31];
};
__device__ Flags g_flags;

__device__ __forceinline__ uint32_t smem_u32(const void* p) { return (uint32_t)__cvta_generic_to_shared(p); }
__device__ __forceinline__ uint32_t pack2(float lo, float hi) {
    uint32_t r; asm("cvt.rn.bf16x2.f32 %0, %1, %2;" : "=r"(r) : "f"(hi), "f"(lo)); return r;
}
__device__ __forceinline__ float bfr(float x) { return __uint_as_float(pack2(0.f, x)); }
__device__ __forceinline__ float inv_std(float var) {
    float s, r; asm("sqrt.approx.f32 %0, %1;" : "=f"(s) : "f"(bfr(bfr(var) + 1e-5f))); asm("rcp.approx.f32 %0, %1;" : "=f"(r) : "f"(bfr(s))); return r;
}
__device__ __forceinline__ float lo_f(uint32_t v) { return __uint_as_float(v << 16); }
__device__ __forceinline__ float hi_f(uint32_t v) { return __uint_as_float(v & 0xffff0000u); }
__device__ __forceinline__ void mbar_init(uint32_t bar, int cnt) { asm volatile("mbarrier.init.shared::cta.b64 [%0], %1;" :: "r"(bar), "r"(cnt) : "memory"); }
__device__ __forceinline__ void mbar_expect(uint32_t bar, int bytes) { asm volatile("mbarrier.arrive.expect_tx.shared::cta.b64 _, [%0], %1;" :: "r"(bar), "r"(bytes) : "memory"); }
__device__ __forceinline__ void mbar_arrive(uint32_t bar) { asm volatile("mbarrier.arrive.shared::cta.b64 _, [%0];" :: "r"(bar) : "memory"); }
constexpr int SPIN_LIMIT = 1 << 18;
__device__ __forceinline__ void mbar_wait(uint32_t bar, uint32_t par) {
    asm volatile("{ .reg .pred p, q; .reg .u32 n; mov.u32 n, 0;\n"
                 "W_%=: mbarrier.try_wait.parity.shared::cta.b64 p, [%0], %1;\n"
                 "@p bra.uni D_%=;\n"
                 "add.u32 n, n, 1; setp.lt.u32 q, n, 0x200000; @q bra.uni W_%=;\n"
                 "trap;\n"
                 "D_%=: }" :: "r"(bar), "r"(par) : "memory");
}
__device__ __forceinline__ void tma2d(uint32_t dst, const CUtensorMap* m, int c0, int c1, uint32_t bar) {
    asm volatile("cp.async.bulk.tensor.2d.shared::cluster.global.mbarrier::complete_tx::bytes [%0], [%1, {%3, %4}], [%2];"
        :: "r"(dst), "l"((uint64_t)m), "r"(bar), "r"(c0), "r"(c1) : "memory");
}
__device__ __forceinline__ uint64_t policy_stream() { uint64_t p; asm("createpolicy.fractional.L2::evict_first.b64 %0, 1.0;" : "=l"(p)); return p; }
__device__ __forceinline__ void tma2d_ef(uint32_t dst, const CUtensorMap* m, int c0, int c1, uint32_t bar, uint64_t pol) {
    asm volatile("cp.async.bulk.tensor.2d.shared::cluster.global.mbarrier::complete_tx::bytes.L2::cache_hint [%0], [%1, {%3, %4}], [%2], %5;"
        :: "r"(dst), "l"((uint64_t)m), "r"(bar), "r"(c0), "r"(c1), "l"(pol) : "memory");
}
__device__ __forceinline__ void tma3d(uint32_t dst, const CUtensorMap* m, int row, int chunk, uint32_t bar) {
    asm volatile("cp.async.bulk.tensor.3d.shared::cluster.global.mbarrier::complete_tx::bytes [%0], [%1, {0, %3, %4}], [%2];"
        :: "r"(dst), "l"((uint64_t)m), "r"(bar), "r"(row), "r"(chunk) : "memory");
}
__device__ __forceinline__ void tma3d_store(const CUtensorMap* m, int row, int chunk, uint32_t src, uint64_t pol, bool hint) {
    if (hint) asm volatile("cp.async.bulk.tensor.3d.global.shared::cta.bulk_group.L2::cache_hint [%0, {0, %2, %3}], [%1], %4;"
        :: "l"((uint64_t)m), "r"(src), "r"(row), "r"(chunk), "l"(pol) : "memory");
    else asm volatile("cp.async.bulk.tensor.3d.global.shared::cta.bulk_group [%0, {0, %2, %3}], [%1];"
        :: "l"((uint64_t)m), "r"(src), "r"(row), "r"(chunk) : "memory");
}
__device__ __forceinline__ bool elect() { uint32_t p; asm volatile("{ .reg .pred e; elect.sync _|e, -1; selp.u32 %0, 1, 0, e; }" : "=r"(p)); return p; }
__device__ __forceinline__ uint2 ld_ef(const void* p, uint64_t pol) {
    uint2 v; asm volatile("ld.relaxed.gpu.global.L2::cache_hint.v2.u32 {%0,%1}, [%2], %3;" : "=r"(v.x), "=r"(v.y) : "l"(p), "l"(pol)); return v;
}
__device__ __forceinline__ void st_ef(void* p, uint2 v, uint64_t pol) {
    asm volatile("st.global.L2::cache_hint.v2.u32 [%0], {%1,%2}, %3;" :: "l"(p), "r"(v.x), "r"(v.y), "l"(pol) : "memory");
}
__device__ __forceinline__ void bulk_g2s(uint32_t dst, const void* src, int bytes, uint32_t bar) {
    asm volatile("cp.async.bulk.shared::cluster.global.mbarrier::complete_tx::bytes [%0], [%1], %2, [%3];" :: "r"(dst), "l"(src), "r"(bytes), "r"(bar) : "memory");
}
__device__ __forceinline__ void bulk_g2s_ef(uint32_t dst, const void* src, int bytes, uint32_t bar, uint64_t pol) {
    asm volatile("cp.async.bulk.shared::cluster.global.mbarrier::complete_tx::bytes.L2::cache_hint [%0], [%1], %2, [%3], %4;" :: "r"(dst), "l"(src), "r"(bytes), "r"(bar), "l"(pol) : "memory");
}
__device__ __forceinline__ void bulk_s2g(void* dst, uint32_t src, int bytes) {
    asm volatile("cp.async.bulk.global.shared::cta.bulk_group [%0], [%1], %2;" :: "l"(dst), "r"(src), "r"(bytes) : "memory");
}
#define BULK_COMMIT()    asm volatile("cp.async.bulk.commit_group;" ::: "memory")
#define BULK_WAIT_READ() asm volatile("cp.async.bulk.wait_group.read 0;" ::: "memory")
#define BULK_WAIT()      asm volatile("cp.async.bulk.wait_group 0;" ::: "memory")
#define PROXY_FENCE()    asm volatile("fence.proxy.async.shared::cta;" ::: "memory")
__device__ __forceinline__ void ldsm4(uint32_t (&r)[4], uint32_t a) {
    asm volatile("ldmatrix.sync.aligned.m8n8.x4.shared.b16 {%0,%1,%2,%3}, [%4];" : "=r"(r[0]), "=r"(r[1]), "=r"(r[2]), "=r"(r[3]) : "r"(a) : "memory");
}
__device__ __forceinline__ void ldsm4t(uint32_t (&r)[4], uint32_t a) {
    asm volatile("ldmatrix.sync.aligned.m8n8.x4.trans.shared.b16 {%0,%1,%2,%3}, [%4];" : "=r"(r[0]), "=r"(r[1]), "=r"(r[2]), "=r"(r[3]) : "r"(a) : "memory");
}
__device__ __forceinline__ void stsm4(uint32_t a, uint32_t r0, uint32_t r1, uint32_t r2, uint32_t r3) {
    asm volatile("stmatrix.sync.aligned.m8n8.x4.shared.b16 [%0], {%1,%2,%3,%4};" :: "r"(a), "r"(r0), "r"(r1), "r"(r2), "r"(r3) : "memory");
}
__device__ __forceinline__ uint32_t movm_t(uint32_t v) { uint32_t r; asm volatile("movmatrix.sync.aligned.m8n8.trans.b16 %0, %1;" : "=r"(r) : "r"(v)); return r; }
__device__ __forceinline__ void mma16(float (&d)[4], uint32_t a0, uint32_t a1, uint32_t a2, uint32_t a3, uint32_t b0, uint32_t b1) {
    asm volatile("mma.sync.aligned.m16n8k16.row.col.f32.bf16.bf16.f32 {%0,%1,%2,%3}, {%4,%5,%6,%7}, {%8,%9}, {%0,%1,%2,%3};"
        : "+f"(d[0]), "+f"(d[1]), "+f"(d[2]), "+f"(d[3]) : "r"(a0), "r"(a1), "r"(a2), "r"(a3), "r"(b0), "r"(b1));
}
__device__ __forceinline__ void mma16(float (&d)[4], const uint32_t (&a)[4], uint32_t b0, uint32_t b1) { mma16(d, a[0], a[1], a[2], a[3], b0, b1); }
__device__ __forceinline__ void mma16z(float (&d)[4], const uint32_t (&a)[4], uint32_t b0, uint32_t b1) {
    asm volatile("mma.sync.aligned.m16n8k16.row.col.f32.bf16.bf16.f32 {%0,%1,%2,%3}, {%4,%5,%6,%7}, {%8,%9}, {%10,%10,%10,%10};"
        : "=f"(d[0]), "=f"(d[1]), "=f"(d[2]), "=f"(d[3]) : "r"(a[0]), "r"(a[1]), "r"(a[2]), "r"(a[3]), "r"(b0), "r"(b1), "f"(0.f));
}
__device__ __forceinline__ void mma8z(float (&d)[4], uint32_t a0, uint32_t a1, uint32_t b0) {
    asm volatile("mma.sync.aligned.m16n8k8.row.col.f32.bf16.bf16.f32 {%0,%1,%2,%3}, {%4,%5}, {%6}, {%7,%7,%7,%7};"
        : "=f"(d[0]), "=f"(d[1]), "=f"(d[2]), "=f"(d[3]) : "r"(a0), "r"(a1), "r"(b0), "f"(0.f));
}
__device__ __forceinline__ void bar_sync(int id, int n) { asm volatile("bar.sync %0, %1;" :: "r"(id), "r"(n) : "memory"); }
__device__ __forceinline__ void bar_arrive(int id, int n) { asm volatile("bar.arrive %0, %1;" :: "r"(id), "r"(n) : "memory"); }
__device__ __forceinline__ uint64_t mkdesc(uint32_t addr, uint32_t lbo, uint32_t sbo) {
    return (uint64_t)((addr & 0x3FFFF) >> 4) | ((uint64_t)(lbo >> 4) << 16) | ((uint64_t)(sbo >> 4) << 32) | (1ull << 62);
}
#define WG_FENCE()  asm volatile("wgmma.fence.sync.aligned;" ::: "memory")
#define WG_COMMIT() asm volatile("wgmma.commit_group.sync.aligned;" ::: "memory")
#define WG_WAIT(n)  asm volatile("wgmma.wait_group.sync.aligned %0;" :: "n"(n) : "memory")

__device__ __forceinline__ void wgmma_ss_n192_tb(float (&d)[96], uint64_t a, uint64_t b, int acc) {
    asm volatile("{ .reg .pred p; setp.ne.b32 p, %98, 0;\n"
        "wgmma.mma_async.sync.aligned.m64n192k16.f32.bf16.bf16 {%0,%1,%2,%3,%4,%5,%6,%7,%8,%9,%10,%11,%12,%13,%14,%15,%16,%17,%18,%19,%20,%21,%22,%23,%24,%25,%26,%27,%28,%29,%30,%31,%32,%33,%34,%35,%36,%37,%38,%39,%40,%41,%42,%43,%44,%45,%46,%47,%48,%49,%50,%51,%52,%53,%54,%55,%56,%57,%58,%59,%60,%61,%62,%63,%64,%65,%66,%67,%68,%69,%70,%71,%72,%73,%74,%75,%76,%77,%78,%79,%80,%81,%82,%83,%84,%85,%86,%87,%88,%89,%90,%91,%92,%93,%94,%95}, %96, %97, p, 1, 1, 0, 1; }"
        : "+f"(d[0]), "+f"(d[1]), "+f"(d[2]), "+f"(d[3]), "+f"(d[4]), "+f"(d[5]), "+f"(d[6]), "+f"(d[7]), "+f"(d[8]), "+f"(d[9]), "+f"(d[10]), "+f"(d[11]), "+f"(d[12]), "+f"(d[13]), "+f"(d[14]), "+f"(d[15]), "+f"(d[16]), "+f"(d[17]), "+f"(d[18]), "+f"(d[19]), "+f"(d[20]), "+f"(d[21]), "+f"(d[22]), "+f"(d[23]), "+f"(d[24]), "+f"(d[25]), "+f"(d[26]), "+f"(d[27]), "+f"(d[28]), "+f"(d[29]), "+f"(d[30]), "+f"(d[31]), "+f"(d[32]), "+f"(d[33]), "+f"(d[34]), "+f"(d[35]), "+f"(d[36]), "+f"(d[37]), "+f"(d[38]), "+f"(d[39]), "+f"(d[40]), "+f"(d[41]), "+f"(d[42]), "+f"(d[43]), "+f"(d[44]), "+f"(d[45]), "+f"(d[46]), "+f"(d[47]), "+f"(d[48]), "+f"(d[49]), "+f"(d[50]), "+f"(d[51]), "+f"(d[52]), "+f"(d[53]), "+f"(d[54]), "+f"(d[55]), "+f"(d[56]), "+f"(d[57]), "+f"(d[58]), "+f"(d[59]), "+f"(d[60]), "+f"(d[61]), "+f"(d[62]), "+f"(d[63]), "+f"(d[64]), "+f"(d[65]), "+f"(d[66]), "+f"(d[67]), "+f"(d[68]), "+f"(d[69]), "+f"(d[70]), "+f"(d[71]), "+f"(d[72]), "+f"(d[73]), "+f"(d[74]), "+f"(d[75]), "+f"(d[76]), "+f"(d[77]), "+f"(d[78]), "+f"(d[79]), "+f"(d[80]), "+f"(d[81]), "+f"(d[82]), "+f"(d[83]), "+f"(d[84]), "+f"(d[85]), "+f"(d[86]), "+f"(d[87]), "+f"(d[88]), "+f"(d[89]), "+f"(d[90]), "+f"(d[91]), "+f"(d[92]), "+f"(d[93]), "+f"(d[94]), "+f"(d[95])
        : "l"(a), "l"(b), "r"(acc));
}

__device__ __forceinline__ void wgmma_ss_n128_tb(float (&d)[64], uint64_t a, uint64_t b, int acc) {
    asm volatile("{ .reg .pred p; setp.ne.b32 p, %66, 0;\n"
        "wgmma.mma_async.sync.aligned.m64n128k16.f32.bf16.bf16 {%0,%1,%2,%3,%4,%5,%6,%7,%8,%9,%10,%11,%12,%13,%14,%15,%16,%17,%18,%19,%20,%21,%22,%23,%24,%25,%26,%27,%28,%29,%30,%31,%32,%33,%34,%35,%36,%37,%38,%39,%40,%41,%42,%43,%44,%45,%46,%47,%48,%49,%50,%51,%52,%53,%54,%55,%56,%57,%58,%59,%60,%61,%62,%63}, %64, %65, p, 1, 1, 0, 1; }"
        : "+f"(d[0]), "+f"(d[1]), "+f"(d[2]), "+f"(d[3]), "+f"(d[4]), "+f"(d[5]), "+f"(d[6]), "+f"(d[7]), "+f"(d[8]), "+f"(d[9]), "+f"(d[10]), "+f"(d[11]), "+f"(d[12]), "+f"(d[13]), "+f"(d[14]), "+f"(d[15]), "+f"(d[16]), "+f"(d[17]), "+f"(d[18]), "+f"(d[19]), "+f"(d[20]), "+f"(d[21]), "+f"(d[22]), "+f"(d[23]), "+f"(d[24]), "+f"(d[25]), "+f"(d[26]), "+f"(d[27]), "+f"(d[28]), "+f"(d[29]), "+f"(d[30]), "+f"(d[31]), "+f"(d[32]), "+f"(d[33]), "+f"(d[34]), "+f"(d[35]), "+f"(d[36]), "+f"(d[37]), "+f"(d[38]), "+f"(d[39]), "+f"(d[40]), "+f"(d[41]), "+f"(d[42]), "+f"(d[43]), "+f"(d[44]), "+f"(d[45]), "+f"(d[46]), "+f"(d[47]), "+f"(d[48]), "+f"(d[49]), "+f"(d[50]), "+f"(d[51]), "+f"(d[52]), "+f"(d[53]), "+f"(d[54]), "+f"(d[55]), "+f"(d[56]), "+f"(d[57]), "+f"(d[58]), "+f"(d[59]), "+f"(d[60]), "+f"(d[61]), "+f"(d[62]), "+f"(d[63])
        : "l"(a), "l"(b), "r"(acc));
}

__device__ __forceinline__ void wgmma_rs_n32(float (&d)[16], const uint32_t (&a)[4], uint64_t b) {
    asm volatile("wgmma.mma_async.sync.aligned.m64n32k16.f32.bf16.bf16 {%0,%1,%2,%3,%4,%5,%6,%7,%8,%9,%10,%11,%12,%13,%14,%15}, {%16,%17,%18,%19}, %20, 1, 1, 1, 0;"
        : "+f"(d[0]), "+f"(d[1]), "+f"(d[2]), "+f"(d[3]), "+f"(d[4]), "+f"(d[5]), "+f"(d[6]), "+f"(d[7]), "+f"(d[8]), "+f"(d[9]), "+f"(d[10]), "+f"(d[11]), "+f"(d[12]), "+f"(d[13]), "+f"(d[14]), "+f"(d[15])
        : "r"(a[0]), "r"(a[1]), "r"(a[2]), "r"(a[3]), "l"(b));
}
__device__ __forceinline__ uint32_t umax3(uint32_t a, uint32_t b, uint32_t c) { return max(max(a, b), c); }
__device__ __forceinline__ void wait_until(uint32_t t) { while ((int32_t)((uint32_t)clock() - t) < 0) {} }
__device__ __forceinline__ uint32_t gtime() { uint32_t c; asm volatile("mov.u32 %0, %%globaltimer_lo;" : "=r"(c)); return c; }
__device__ __forceinline__ uint32_t opaque(uint32_t v) { uint32_t r; asm volatile("shfl.sync.bfly.b32 %0, %1, 0, 31, -1;" : "=r"(r) : "r"(v)); return r; }
__device__ __forceinline__ uint32_t lds32(uint32_t a) { uint32_t v; asm volatile("ld.shared.u32 %0, [%1];" : "=r"(v) : "r"(a) : "memory"); return v; }
__device__ __forceinline__ void sts32(uint32_t a, uint32_t v) { asm volatile("st.shared.u32 [%0], %1;" :: "r"(a), "r"(v) : "memory"); }
__device__ __forceinline__ void lds64(uint32_t (&v)[2], uint32_t a) { asm volatile("ld.shared.v2.u32 {%0,%1}, [%2];" : "=r"(v[0]), "=r"(v[1]) : "r"(a) : "memory"); }
__device__ __forceinline__ void lds128(uint32_t (&v)[4], uint32_t a) { asm volatile("ld.shared.v4.u32 {%0,%1,%2,%3}, [%4];" : "=r"(v[0]), "=r"(v[1]), "=r"(v[2]), "=r"(v[3]) : "r"(a) : "memory"); }
__device__ __forceinline__ void sts128(uint32_t a, uint32_t x, uint32_t y, uint32_t z, uint32_t w) { asm volatile("st.shared.v4.u32 [%0], {%1,%2,%3,%4};" :: "r"(a), "r"(x), "r"(y), "r"(z), "r"(w) : "memory"); }
__device__ __forceinline__ float2 lds64f(uint32_t a) { float2 v; asm volatile("ld.shared.v2.f32 {%0,%1}, [%2];" : "=f"(v.x), "=f"(v.y) : "r"(a) : "memory"); return v; }
__device__ __forceinline__ float4 lds128f(uint32_t a) { float4 v; asm volatile("ld.shared.v4.f32 {%0,%1,%2,%3}, [%4];" : "=f"(v.x), "=f"(v.y), "=f"(v.z), "=f"(v.w) : "r"(a) : "memory"); return v; }
__device__ __forceinline__ void sts128f(uint32_t a, float x, float y, float z, float w) { asm volatile("st.shared.v4.f32 [%0], {%1,%2,%3,%4};" :: "r"(a), "f"(x), "f"(y), "f"(z), "f"(w) : "memory"); }

__device__ __forceinline__ float warp_sum(float v) {
#pragma unroll
    for (int o = 16; o; o >>= 1) v += __shfl_xor_sync(0xffffffffu, v, o);
    return v;
}
__device__ __forceinline__ void ln_mod(const float (&xv)[20], const uint32_t (&sv)[10], const uint32_t (&tv)[10], float (&hv)[20]) {
    float s = 0;
#pragma unroll
    for (int i = 0; i < 20; i++) s += xv[i];
    const float mean = warp_sum(s) * (1.f / DM);
    float q = 0;
#pragma unroll
    for (int i = 0; i < 20; i++) { float d = xv[i] - mean; q += d * d; }
    const float mb = bfr(mean), inv = inv_std(warp_sum(q) * (1.f / DM));
#pragma unroll
    for (int i = 0; i < 10; i++) {
        const float n0 = bfr(bfr(xv[2 * i] - mb) * inv), n1 = bfr(bfr(xv[2 * i + 1] - mb) * inv);
        hv[2 * i] = bfr(bfr(n0 * bfr(1.f + lo_f(sv[i]))) + lo_f(tv[i]));
        hv[2 * i + 1] = bfr(bfr(n1 * bfr(1.f + hi_f(sv[i]))) + hi_f(tv[i]));
    }
}
__device__ __forceinline__ uint32_t ld_rlx(const uint32_t* f) { uint32_t v; asm volatile("ld.relaxed.gpu.global.u32 %0, [%1];" : "=r"(v) : "l"(f) : "memory"); return v; }
__device__ __forceinline__ void bump(uint32_t* f) { asm volatile("red.relaxed.gpu.global.add.u32 [%0], 1;" :: "l"(f) : "memory"); }
__device__ __forceinline__ void flag_wait(const uint32_t* f, uint32_t target) {
    for (int n = 0;; n++) {
        uint32_t v; asm volatile("ld.relaxed.gpu.global.u32 %0, [%1];" : "=r"(v) : "l"(f) : "memory");
        if (v >= target) break;
        if (n > (1 << 23)) __trap();
    }
}
__device__ __forceinline__ void flag_add(uint32_t* f, uint32_t v = 1) { asm volatile("red.release.gpu.global.add.u32 [%0], %1;" :: "l"(f), "r"(v) : "memory"); }
constexpr int N_SIDE = 132;
__device__ __forceinline__ void flags_release() {
    uint32_t old; asm volatile("atom.acq_rel.gpu.global.add.u32 %0, [%1], 1;" : "=r"(old) : "l"(&g_flags.done) : "memory");
    if (old == 96 + N_SIDE - 1) { g_flags.mod = 0; g_flags.h = 0; g_flags.done = 0; }
}

struct ChainMaps { CUtensorMap wq, wk, wv, wo, h1, h4, wmod; };
struct ChainArgs { const bf16 *x, *mem0, *c, *wv, *wo; int D, force; };
constexpr uint32_t SM_BASE = 1024;
constexpr int C_WV = 0, C_WO = 81920, C_XR = 167936, C_QX = C_XR + 4 * 4096, C_KX = C_XR + 9 * 4096, C_VX = C_XR + 40960, C_VP = C_VX, C_MEM = C_VX + 4096,
              C_QM = C_MEM + 10240, C_KM = C_QM + 1024, C_VM = C_KM + 1024, C_OX = C_VM + 1024, C_SC = C_OX + 3072, C_BAR = C_SC + 1920, C_SMEM = C_BAR + 256;
constexpr int CB_W = C_BAR, CB_W2 = C_BAR + 8, CB_SC = C_BAR + 16, CB_OX = C_BAR + 24, CB_VX = C_BAR + 32, CB_XF = C_BAR + 40, CB_XG = C_BAR + 48, CB_PRE = C_BAR + 56,
              C_MAX = C_BAR + 64, C_SCL = C_BAR + 80, C_BAD = C_BAR + 84;
static_assert(C_SMEM <= 232448, "chain shared memory");
enum { B_MEM = 1, B_QK, B_VP, B_OWN, B_RED, B_X, B_AUX };
constexpr int NP = 8;
constexpr int NW = 8;
constexpr int BD = 2, VD = 1, OD = 4;
#define PROF(i)
#define PROFG(i)
#define PROFV(i, v)
#define SFENCE() asm volatile("griddepcontrol.launch_dependents;" ::: "memory")
#define PIN(x) asm volatile("" : "+r"(x))
#define PINL(x) asm volatile("" : "+l"(x))
__host__ __device__ constexpr bool pair_v(int i) { return i == 0 || (i % 3 == 2 && i < 9); }
__host__ __device__ constexpr bool pair_own(int i) { return pair_v(i) || i >= 14; }
__host__ __device__ constexpr int pair_idx(int i) { return pair_v(i) ? (i + 1) / 3 : i < 14 ? i - (i < 9 ? i / 3 + 1 : 4) : i - 10; }

__device__ __forceinline__ uint32_t packh(float lo, float hi) { uint32_t r; asm("cvt.rn.f16x2.f32 %0, %1, %2;" : "=r"(r) : "f"(hi), "f"(lo)); return r; }
__device__ __forceinline__ uint32_t h2b(uint32_t v) {
    uint32_t r; asm("{ .reg .f16 a, b; .reg .f32 x, y; mov.b32 {a, b}, %1; cvt.f32.f16 x, a; cvt.f32.f16 y, b; cvt.rn.bf16x2.f32 %0, y, x; }" : "=r"(r) : "r"(v)); return r;
}
__device__ __forceinline__ uint32_t h2b_lo(uint32_t u, uint32_t v) {
    uint32_t r; asm("{ .reg .f16 a, b, c, d; .reg .f32 x, y; mov.b32 {a, b}, %1; mov.b32 {c, d}, %2; cvt.f32.f16 x, a; cvt.f32.f16 y, c; cvt.rn.bf16x2.f32 %0, y, x; }" : "=r"(r) : "r"(u), "r"(v)); return r;
}
constexpr float SCL2E = 0.07216878364870322f * 1.4426950408889634f;
__device__ __forceinline__ uint32_t score_tile(const uint32_t (&qa)[2][4], const uint32_t (&kb)[2][4]) {
    float u[4], v[4], x[4], y[4];
    mma16z(u, qa[0], kb[0][0], kb[0][1]); mma16z(v, qa[0], kb[0][2], kb[0][3]);
    mma16z(x, qa[1], kb[1][0], kb[1][1]); mma16z(y, qa[1], kb[1][2], kb[1][3]);
    return pack2(((u[0] + v[2]) + (x[0] + y[2])) * SCL2E, ((u[1] + v[3]) + (x[1] + y[3])) * SCL2E);
}
__device__ __forceinline__ void score_tiles(const uint32_t (&qa)[2][4], const uint32_t (&kb)[2][4], const uint32_t (&km)[2][4], uint32_t& a, uint32_t& b) {
    float u[4], v[4], x[4], y[4];
    mma16z(u, qa[0], kb[0][0], kb[0][1]); mma16z(v, qa[0], kb[0][2], kb[0][3]); mma16z(x, qa[0], km[0][0], km[0][1]); mma16z(y, qa[0], km[0][2], km[0][3]);
    mma16(u, qa[1], kb[1][0], kb[1][1]); mma16(v, qa[1], kb[1][2], kb[1][3]); mma16(x, qa[1], km[1][0], km[1][1]); mma16(y, qa[1], km[1][2], km[1][3]);
    a = pack2((u[0] + v[2]) * SCL2E, (u[1] + v[3]) * SCL2E); b = pack2((x[0] + y[2]) * SCL2E, (x[1] + y[3]) * SCL2E);
}
__device__ __forceinline__ void stas1(uint32_t dst, uint32_t x, uint32_t bar) {
    asm volatile("st.async.shared::cluster.mbarrier::complete_tx::bytes.b32 [%0], %1, [%2];" :: "r"(dst), "r"(x), "r"(bar) : "memory");
}
__device__ __forceinline__ void stas2(uint32_t dst, uint32_t x, uint32_t y, uint32_t bar) {
    asm volatile("st.async.shared::cluster.mbarrier::complete_tx::bytes.v2.b32 [%0], {%1,%2}, [%3];" :: "r"(dst), "r"(x), "r"(y), "r"(bar) : "memory");
}
__device__ __forceinline__ float ex2(float x) { float r; asm volatile("ex2.approx.ftz.f32 %0, %1;" : "=f"(r) : "f"(x)); return r; }
__device__ __forceinline__ void h_fetch_a(const ChainMaps& mp, uint32_t sm, int n) {
    mbar_expect(sm + CB_XF, 32768);
    tma3d(sm + C_XR, &mp.h4, n * SEG, 0, sm + CB_XF); tma3d(sm + C_XR + 20480, &mp.h4, n * SEG, 5, sm + CB_XF);
}
__device__ __forceinline__ void h_fetch_b(const ChainMaps& mp, uint32_t sm, int n) {
    mbar_expect(sm + CB_XG, 8192);
    tma3d(sm + C_QX, &mp.h1, n * SEG, 4, sm + CB_XG); tma3d(sm + C_KX, &mp.h1, n * SEG, 9, sm + CB_XG);
}
__device__ __forceinline__ uint32_t absmax2(uint32_t a, uint32_t b) {
    uint32_t r; asm("max.u16x2 %0, %1, %2;" : "=r"(r) : "r"(a), "r"(b & 0x7fff7fffu)); return r;
}

__global__ void __cluster_dims__(3, 1, 1) __launch_bounds__(384, 1) k_chain(const __grid_constant__ ChainMaps mp, const __grid_constant__ ChainArgs ar) {
    extern __shared__ __align__(1024) uint8_t smraw[];
    const uint32_t sm = SM_BASE + ((blockIdx.x % 3) << 24);
    if (smem_u32(smraw) != sm) __trap();
    uint32_t tid; asm volatile("mov.u32 %0, %%tid.x;" : "=r"(tid));
    const int warp = __shfl_sync(0xffffffffu, tid >> 5, 0), lane = tid & 31, wg = warp >> 2, w = warp & 3;
    const int blk = blockIdx.x, head = blk / 3, j = blk % 3;
    const int col0 = head * DH + j * 64, u0 = 7 * j, nu = j == 2 ? 6 : 7;
    asm volatile("griddepcontrol.launch_dependents;");
#define PPROF(i)
    PPROF(0);
    {
        const int mc0 = (blk >> 1) * 80 + (blk & 1) * 32, mcn = (blk & 1) ? 24 : 16;
        const int nrow = blk < 74 ? 2 : blk == 74 ? (warp < 8 ? 2 : 1) : 1;
        if (tid == 0) {
            mbar_init(sm + CB_PRE, 1);
            asm volatile("fence.mbarrier_init.release.cluster;" ::: "memory");
            const int n1 = blk < 74 ? 15360 : blk == 74 ? 10240 : 0;
            mbar_expect(sm + CB_PRE, 61440 + 1280 + 15360 + n1);
            bulk_g2s(sm + C_QM, ar.c, 1280, sm + CB_PRE);
#pragma unroll 1
            for (int c = 0; c < 4; c++) tma2d(sm + C_WO + 24576 + c * 15360, &mp.wmod, mc0, c * 160, sm + CB_PRE);
            bulk_g2s(sm + C_XR, ar.x + blk * 12 * DM, 15360, sm + CB_PRE);
            if (n1) bulk_g2s(sm + C_XR + 15360, ar.x + (1152 + blk * 12) * DM, n1, sm + CB_PRE);
        }
        if (tid == 32) {
#pragma unroll 1
            for (int c = 0; c < 7; c++) mbar_init(sm + C_BAR + 8 * c, c == 2 ? 5 : 1);
            asm volatile("fence.mbarrier_init.release.cluster;" ::: "memory");
            mbar_expect(sm + CB_SC, 1280); mbar_expect(sm + CB_OX, 2048);
        }
#pragma unroll 1
        for (int i = blk * 384 + tid; i < 32 * 1600; i += 96 * 384) ((uint4*)g_acc)[i / 1600 * 2048 + i % 1600] = make_uint4(0, 0, 0, 0);
        if (tid < 12 && blk * 12 + tid < (int)(offsetof(Flags, mod) / 16)) ((uint4*)&g_flags)[blk * 12 + tid] = make_uint4(0, 0, 0, 0);
        static_assert(offsetof(Flags, mod) <= 96 * 12 * 16, "flags");
        PPROF(8);
        asm volatile("barrier.cluster.arrive.release.aligned; barrier.cluster.wait.acquire.aligned;" ::: "memory");
        PPROF(9);
        mbar_wait(sm + CB_PRE, 0);
        PPROF(10);
        if (tid == 352) {
            const uint64_t ef = policy_stream();
            mbar_expect(sm + CB_W, 2 * 81920);
#pragma unroll 1
            for (int c = 0; c < 10; c++) tma2d_ef(sm + C_WV + c * 8192, &mp.wq, col0, c * 64, sm + CB_W, ef);
        }
        if (tid < 320) {
            const uint32_t cv = lds32(sm + C_QM + tid * 4);
            asm volatile("st.shared.v2.f32 [%0], {%1,%2};" :: "r"(sm + C_VP + tid * 8), "f"(bfr(__fdividef(lo_f(cv), 1.f + __expf(-lo_f(cv))))),
                         "f"(bfr(__fdividef(hi_f(cv), 1.f + __expf(-hi_f(cv))))) : "memory");
        }
        __syncthreads();
        {
            float a0 = 0, a1 = 0;
            const uint32_t k0 = (tid / 24) * 40, wa0 = sm + C_WO + 24576 + k0 * 96 + (tid % 24) * 4;
#pragma unroll 4
            for (int i = 0; i < 40; i++) {
                const float sc = __uint_as_float(lds32(sm + C_VP + (k0 + i) * 4));
                const uint32_t wv = lds32(wa0 + i * 96);
                a0 += sc * lo_f(wv); a1 += sc * hi_f(wv);
            }
            asm volatile("st.shared.v2.f32 [%0], {%1,%2};" :: "r"(sm + C_MEM + tid * 8), "f"(a0), "f"(a1) : "memory");
        }
        __syncthreads();
        PPROF(11);
        if (warp == 0) {
            float a0 = 0, a1 = 0;
            const int cp = lane < mcn ? lane : 0;
#pragma unroll 4
            for (int i = 0; i < 16; i++) { const float2 v = lds64f(sm + C_MEM + (i * 24 + cp) * 8); a0 += v.x; a1 += v.y; }
            uint32_t* dst = (uint32_t*)(g_mod + mc0) + cp;
            *dst = pack2(a0, a1);
            const uint32_t rb = ld_rlx(dst);
            PPROF(1);
            if (__all_sync(0xffffffffu, rb == pack2(a0, a1)) && tid == 0) bump(blk < 32 ? &g_flags.mod : &g_flags.h);
            if (tid == 0) flag_wait(&g_flags.mod, 32);
            PPROF(2);
        }
        __syncthreads();
        uint32_t sv[10], tv[10], bad = 0;
#pragma unroll
        for (int i = 0; i < 10; i++) { sv[i] = __ldcg((const uint32_t*)g_mod + DM / 2 + lane + 32 * i); tv[i] = __ldcg((const uint32_t*)g_mod + lane + 32 * i); }
#pragma unroll 1
        for (int q = 0; q < nrow; q++) {
            float xv[20], hv[20];
#pragma unroll
            for (int i = 0; i < 10; i++) { const uint32_t v = lds32(sm + C_XR + q * 15360 + warp * 1280 + lane * 4 + i * 128); xv[2 * i] = lo_f(v); xv[2 * i + 1] = hi_f(v); }
            ln_mod(xv, sv, tv, hv);
            uint32_t* dst = (uint32_t*)g_h + (q * 1152 + blk * 12 + warp) * (DM / 2) + lane;
#pragma unroll
            for (int i = 0; i < 10; i++) dst[32 * i] = pack2(hv[2 * i], hv[2 * i + 1]);
#pragma unroll
            for (int i = 0; i < 10; i++) bad |= ld_rlx(dst + 32 * i) ^ pack2(hv[2 * i], hv[2 * i + 1]);
        }
        if (__syncthreads_or(bad)) __trap();
        PPROF(3);
        if (tid == 0) {
            bump(&g_flags.h);
            flag_wait(&g_flags.h, 160);
            h_fetch_a(mp, sm, 0); h_fetch_b(mp, sm, 0);
            const uint64_t ef = policy_stream();
#pragma unroll 1
            for (int c = 0; c < 10; c++) tma2d_ef(sm + C_WO + c * 8192, &mp.wk, col0, c * 64, sm + CB_W, ef);
        }
        if (tid == 0) flags_release();
        PPROF(4);
        __syncthreads();
        if (tid >= 64) {
#pragma unroll 1
            for (int i = tid - 64; i < 640 + 192 * 4; i += 320)
                asm volatile("prefetch.global.L2 [%0];" :: "l"(i < 640 ? ar.wv + (size_t)i * HD + col0 : ar.wo + (size_t)(head * DH + ((i - 640) >> 2)) * DM + u0 * 32 + min((i & 3) * 64, 639 - u0 * 32)));
        }
    }
    const int r = lane & 7, mi = lane >> 3;
    uint8_t* const rec0 = g_rec + (size_t)head * REC;
    if (wg < 2) {
        asm volatile("setmaxnreg.inc.sync.aligned.u32 224;");
        const uint32_t l16 = opaque(sm + lane * 16);
        uint32_t wa[40][4], pl[NP][4];
        const uint32_t wfrag = ((mi >> 1) * 8 + r) * 128 + (((2 * w + (mi & 1)) ^ r) << 4);
        mbar_wait(sm + CB_W, 0);
#pragma unroll
        for (int i = 0; i < 40; i++)
            ldsm4t(wa[i], sm + (wg == 0 ? C_WV : C_WO) + wfrag + ((pair_own(i >> 1) ? wg : 1 - wg) * 20 + pair_idx(i >> 1) * 2 + (i & 1)) * 2048);
        PPROF(5);
        bar_arrive(B_OWN, 384);
        mbar_wait(sm + CB_W2, 0);
        PPROF(7);
        const uint32_t wvrd = opaque(sm + C_WV + wfrag + wg * 40960);
        const uint32_t word = opaque(sm + C_WO + warp * 12288 + ((mi >> 1) * 8 + r) * 64 + (((mi & 1) ^ (r >> 1)) << 4));
        const uint32_t own = wg * 5120, oth = 5120 - own;
        mbar_wait(sm + CB_XF, 0);
#pragma unroll 1
        for (int s = -1;;) {
            uint64_t xo = mkdesc(SM_BASE + C_XR + wg * 20480, 16, 1024), xt = mkdesc(SM_BASE + C_XR + 20480 - wg * 20480, 16, 1024);
            if (s >= 0) {
                float dv[2][4], d[4][4], u[4], isc;
                uint32_t b[20][4], l4;
                const uint32_t mo = l16 + C_MEM + own, mt = l16 + C_MEM + oth;
                bar_sync(B_MEM, 384);
#pragma unroll
                for (int i = 0; i < BD; i++) ldsm4t(b[i], (pair_own(i) ? mo : mt) + pair_idx(i) * 512);
                if (warp == 0) { PROF(0); PROFG(24); }
#pragma unroll
                for (int i = 0; i < 20; i++) {
                    const int c = i < 3 ? 0 : (i & 1) * 2, p = 2 * pair_idx(i);
                    SFENCE();
                    if (i + BD < 20) ldsm4t(b[i + BD], (pair_own(i + BD) ? mo : mt) + pair_idx(i + BD) * 512);
                    if (i > 0 && pair_v(i)) { mma16(dv[0], pl[p % NP], b[i][0], b[i][1]); mma16(dv[1], pl[(p + 1) % NP], b[i][2], b[i][3]); }
                    if (i == 0 || i == 3) { mma16z(d[c], wa[2 * i], b[i][0], b[i][1]); mma16z(d[c + 1], wa[2 * i + 1], b[i][2], b[i][3]); }
                    else { mma16(d[c], wa[2 * i], b[i][0], b[i][1]); mma16(d[c + 1], wa[2 * i + 1], b[i][2], b[i][3]); }
                    if (i == 0) { mma16z(dv[0], pl[0], b[i][0], b[i][1]); mma16z(dv[1], pl[1], b[i][2], b[i][3]); }
                    if (i == 12) isc = __uint_as_float(lds32(sm + C_SCL));
                    if (i == 17) { l4 = l16; PIN(l4); l4 = (l4 >> 2) & 127; PIN(l4); }
                }
                SFENCE();
#pragma unroll
                for (int i = 0; i < 4; i++) u[i] = fmaf(d[2][i] + d[3][i], isc, (d[0][i] + d[1][i]) * isc);
                const uint32_t qs = sm + C_QM + warp * 256 + l4;
                sts32(qs, pack2(u[0], u[1])); sts32(qs + 128, pack2(u[2], u[3]));
                if (warp == 2) PROF(1);
                bar_sync(B_QK, 384);
                if (lds32(sm + C_BAD)) {
                    if (warp < nu) {
                        float e[2][4] = {{0, 0, 0, 0}, {0, 0, 0, 0}};
#pragma unroll 1
                        for (int k = 0; k < 12; k++) {
                            uint32_t ob[2]; lds64(ob, sm + C_OX + k * 256 + l4 * 2);
                            ldsm4t(pl[0], word + k * 1024); ldsm4t(pl[1], (word ^ 32) + k * 1024);
                            mma16(e[0], pl[0], ob[0], ob[1]); mma16(e[1], pl[1], ob[0], ob[1]);
                        }
                        float4* dst = (float4*)(g_slow + (((s & 1) * NH + head) * 20 + u0 + warp) * 256 + l4 * 2);
                        dst[0] = make_float4(e[0][0] * isc, e[0][1] * isc, e[0][2] * isc, e[0][3] * isc); dst[1] = make_float4(e[1][0] * isc, e[1][1] * isc, e[1][2] * isc, e[1][3] * isc);
                        __threadfence();
                    }
                    bar_arrive(B_RED, 384);
#pragma unroll
                    for (int i = 0; i < NP; i++) ldsm4t(pl[i], wvrd + i * 2048);
                    continue;
                }
                {
                    uint32_t a[20][4];
#pragma unroll
                    for (int f = NP; f < NP + VD; f++) ldsm4t(a[f], wvrd + f * 2048);
#pragma unroll
                    for (int f = NP; f < 20; f++) {
                        SFENCE();
                        if (f + VD < 20) ldsm4t(a[f + VD], wvrd + (f + VD) * 2048);
                        mma16(dv[f & 1], a[f], b[10 + (f >> 1)][2 * (f & 1)], b[10 + (f >> 1)][2 * (f & 1) + 1]);
                    }
                    sts128f(l16 + C_VP + warp * 512, (dv[0][0] + dv[1][0]) * isc, (dv[0][1] + dv[1][1]) * isc, (dv[0][2] + dv[1][2]) * isc, (dv[0][3] + dv[1][3]) * isc);
                    if (warp == 0) PROF(2);
                }
                if (warp >= nu || s + 1 == NSEG) {
                    if (warp == 7 && elect()) BULK_WAIT();
                    __syncwarp();
                    bar_arrive(B_VP, 384);
                    if (s + 1 < NSEG) bar_arrive(B_RED, 384);
                    uint8_t* rec = rec0 + (size_t)s * (NH * REC);
                    if (warp == 7 && elect()) {
                        if (s > 0) bump(&g_flags.seg[(s - 1) * 32 + head]);
                        PROXY_FENCE();
                        bulk_s2g(rec + R_Q + j * R_J, sm + C_QX, 4096); bulk_s2g(rec + R_K + j * R_J, sm + C_KX, 4096); bulk_s2g(rec + R_KM + j * R_J, sm + C_KM, 1024);
                        BULK_COMMIT();
                    }
                    __syncwarp();
                    if (s + 1 < NSEG) mbar_wait(sm + CB_XF, (s + 1) & 1);
                    bar_sync(B_OWN, 384);
                    if (warp == 7 && elect()) {
                        if (s + 1 < NSEG) {
                            mbar_expect(sm + CB_VX, 4096);
                            bulk_g2s(sm + C_VX, rec + NH * REC + j * 4096, 4096, sm + CB_VX);
                            BULK_WAIT_READ();
                            h_fetch_b(mp, sm, s + 1);
                        }
                        PROXY_FENCE();
                        bulk_s2g(rec + R_VM + j * R_J, sm + C_VM, 1024);
                        BULK_COMMIT();
                        if (s + 3 < NSEG) {
                            const uint8_t* ln = g_acc + ((s + 3) >> 1) * 32768 + ((s + 3) & 1) * 128 + blk * 256;
                            asm volatile("prefetch.global.L2 [%0];" :: "l"(ln) : "memory");
                            if (blk < 4) asm volatile("prefetch.global.L2 [%0];" :: "l"(ln + 96 * 256) : "memory");
                        }
                        if (s + 2 < NSEG) {
                            if (blk < 10) asm volatile("cp.async.bulk.prefetch.L2.global [%0], 4096;" :: "l"(g_h + (s + 2) * SEG * DM + blk * 2048) : "memory");
                            if ((s & 3) == 2) flag_wait(&g_flags.v[((s + 2) >> 2) * 32 + head], 2);
                            asm volatile("cp.async.bulk.prefetch.L2.global [%0], 4096;" :: "l"(rec + 2 * NH * REC + j * 4096) : "memory");
                        }
                        if (s + 1 == NSEG) { BULK_WAIT(); bump(&g_flags.seg[s * 32 + head]); }
                    }
                    __syncwarp();
                    if (s + 1 == NSEG) break;
                } else {
                    uint32_t w1 = word; PIN(w1); w1 ^= 32;
                    auto frag = [&](int f) { return ((f & 1) ? w1 : word) + (f >> 1) * 1024; };
                    uint32_t a[24][4];
                    bar_arrive(B_VP, 384);
                    uint8_t* acc = g_acc + ((s + 1) >> 1) * 32768 + ((s + 1) & 1) * 128 + (u0 + warp) * 1280;
                    uint32_t ln = l16; PIN(ln); ln = ln >> 4 & 31;
                    uint32_t ox = sm + C_OX + ln * 8;
                    uint8_t* a4 = acc + (ln >> 3) * 256 + (ln & 7) * 16; uint8_t* a1 = acc + 1024 + ln * 4;
                    PIN(ox); PINL(a4); PINL(a1);
                    mbar_wait(sm + CB_XF, (s + 1) & 1);
#pragma unroll
                    for (int f = 0; f < NW; f++) ldsm4t(a[f], frag(f));
                    float e[2][4];
                    uint32_t ob[12][2];
                    bar_sync(B_OWN, 384);
#pragma unroll
                    for (int k = 0; k < 4; k++) lds64(ob[k], ox + k * 256);
#pragma unroll
                    for (int k = 0; k < 4; k++) {
                        SFENCE();
                        if (k > 0) { ldsm4t(a[2 * k - 2 + NW], frag(2 * k - 2 + NW)); ldsm4t(a[2 * k - 1 + NW], frag(2 * k - 1 + NW)); }
                        if (k == 0) { mma16z(e[0], a[0], ob[0][0], ob[0][1]); mma16z(e[1], a[1], ob[0][0], ob[0][1]); }
                        else { mma16(e[0], a[2 * k], ob[k][0], ob[k][1]); mma16(e[1], a[2 * k + 1], ob[k][0], ob[k][1]); }
                    }
                    SFENCE();
                    ldsm4t(a[6 + NW], frag(6 + NW)); ldsm4t(a[7 + NW], frag(7 + NW));
                    PINL(xo); PINL(xt);
                    if (warp == 0) PROF(3);
                    mbar_wait(sm + CB_OX, s & 1);
#pragma unroll
                    for (int k = 4; k < 4 + OD; k++) lds64(ob[k], ox + k * 256);
                    if (warp == 1) PROF(4);
#pragma unroll
                    for (int k = 4; k < 12; k++) {
                        SFENCE();
                        if (k > 4 && k - 1 + OD < 12) lds64(ob[k - 1 + OD], ox + (k - 1 + OD) * 256);
                        if (k > 4 && 2 * k - 2 + NW < 24) { ldsm4t(a[2 * k - 2 + NW], frag(2 * k - 2 + NW)); ldsm4t(a[2 * k - 1 + NW], frag(2 * k - 1 + NW)); }
                        mma16(e[0], a[2 * k], ob[k][0], ob[k][1]); mma16(e[1], a[2 * k + 1], ob[k][0], ob[k][1]);
                    }
                    asm volatile("red.relaxed.gpu.global.add.noftz.v4.f16x2 [%0], {%1,%2,%3,%4};" :: "l"(a4), "r"(packh(e[0][0], e[0][1])), "r"(packh(e[0][2], e[0][3])),
                                 "r"(packh(e[1][0], e[1][1])), "r"(packh(e[1][2], 1.f)) : "memory");
                    asm volatile("red.relaxed.gpu.global.add.noftz.f16x2 [%0], %1;" :: "l"(a1), "r"(packh(e[1][3], 1.f)) : "memory");
                    bar_arrive(B_RED, 384);
                    if (warp == 0) { PROF(5); PROFG(25); }
                }
            }
            float acc[16];
#pragma unroll
            for (int i = 0; i < 16; i++) acc[i] = 0.f;
            if (warp == 1) PROF(12);
            WG_FENCE();
#pragma unroll
            for (int n = 0; n < 40; n++) {
                const int i = n < 24 ? n : n < 32 ? n + 4 : n < 36 ? n - 8 : n, ks = pair_idx(i >> 1) * 2 + (i & 1);
                if (n == 32) mbar_wait(sm + CB_XG, (s + 1) & 1);
                wgmma_rs_n32(acc, wa[i], (pair_own(i >> 1) ? xo : xt) + (((ks >> 2) * 4096 + (ks & 3) * 32) >> 4));
                if (n % 4 == 2 && n / 4 < NP) { SFENCE(); ldsm4t(pl[n / 4], wvrd + n / 4 * 2048); }
            }
            WG_COMMIT();
            WG_WAIT(0);
            if (warp == 1) PROF(13);
            bar_sync(B_X, 256);
            uint32_t lx = l16; PIN(lx);
            const uint32_t dst = (lx ^ (lx >> 3 & 48)) + C_QX + wg * 20480 + w * 1024;
            sts128(dst, pack2(acc[0], acc[1]), pack2(acc[4], acc[5]), pack2(acc[8], acc[9]), pack2(acc[12], acc[13]));
            sts128(dst + 512, pack2(acc[2], acc[3]), pack2(acc[6], acc[7]), pack2(acc[10], acc[11]), pack2(acc[14], acc[15]));
            if (warp == 1) PROF(14);
            s++;
        }
    } else {
        asm volatile("setmaxnreg.dec.sync.aligned.u32 56;");
        const uint32_t l16 = opaque(sm + lane * 16);
        bar_sync(B_OWN, 384);
        if (w == 0 && elect()) {
            mbar_expect(sm + CB_W2, 81920 + nu * 12288);
#pragma unroll 1
            for (int c = 0; c < 10; c++) tma2d(sm + C_WV + c * 8192, &mp.wv, col0, c * 64, sm + CB_W2);
        }
        if (w == 1 && elect()) {
#pragma unroll 1
            for (int c = 0; c < 3 * nu; c++) tma2d(sm + C_WO + c * 4096, &mp.wo, (u0 + c / 3) * 32, head * DH + (c + j) % 3 * 64, sm + CB_W2);
        }
        if (w == 2 && elect()) {
            flag_wait(&g_flags.v[head], 2);
            mbar_expect(sm + CB_VX, 4096);
            bulk_g2s(sm + C_VX, rec0 + j * 4096, 4096, sm + CB_VX);
        }
        __syncwarp();
        uint32_t mx;
        {
            mx = 0;
#pragma unroll 1
            for (int i = 0; i < 20; i++) {
                const int o = w * 20 + i, c = o * 8 + (lane >> 2), t = (lane & 3) * 2;
                const uint32_t v = (uint32_t)__ldg((const unsigned short*)ar.mem0 + t * DM + c) | (uint32_t)__ldg((const unsigned short*)ar.mem0 + (t + 1) * DM + c) << 16;
                sts32(sm + C_MEM + o * 128 + lane * 4, v); mx = absmax2(mx, v);
            }
            sts32(sm + C_SCL, 0x3f800000u);
        }
        int ex = 0;
        bool chk = false;
        int nslow = 0;
        uint32_t vb[2][4];
        { const uint32_t vxrd = l16 + lane * 112 + (((2 * w) ^ vswz(lane)) << 4); mbar_wait(sm + CB_VX, 0); ldsm4t(vb[0], vxrd + C_VX); ldsm4t(vb[1], (vxrd ^ 16) + C_VX); }
        bar_sync(B_MEM, 384);
        for (int s = 0; s < NSEG; s++) {
            uint32_t lq = l16; PIN(lq);
            const uint32_t l0 = lq >> 4 & 31, r0 = l0 & 7, m0 = l0 >> 3;
            uint32_t kb[2][4];
            const uint32_t kxrd = sm + C_KX + l0 * 64 + ((w ^ (r0 >> 1)) << 4);
            ldsm4t(kb[0], kxrd); ldsm4t(kb[1], kxrd + 2048);
            if (w == 0 && s + 1 < NSEG && elect()) h_fetch_a(mp, sm, s + 1);
            __syncwarp();
            const uint32_t r1 = j == 2 ? -(2 << 24) : 1 << 24, r2 = j == 0 ? 2 << 24 : -(1 << 24);
            uint32_t qrd = sm + C_QM + ((m0 >> 1) + 2 * (m0 & 1)) * 128 + r0 * 16, scdst = sm + C_SC + j * 640 + w * 128 + ((l0 * 4) ^ (w * 32)),
                     sc1 = scdst + r1, sc2 = scdst + r2;
            PIN(qrd); PIN(scdst); PIN(sc1); PIN(sc2);
            for (;;) {
                sts32(sm + C_MAX + w * 4, __reduce_max_sync(0xffffffffu, max(mx & 0xffffu, mx >> 16)) >> 7);
                bar_sync(B_AUX, 128);
                uint32_t m4[4]; lds128(m4, sm + C_MAX);
                const int m = __shfl_sync(0xffffffffu, max(max(m4[0], m4[1]), max(m4[2], m4[3])), 0);
                const bool bad = chk && (m == 255 || m < 127 - 6 || ar.force);
                ex = min(max(ex + 130 - m, -40), 40);
                sts32(sm + C_BAD, bad);
                if (!bad) break;
                bar_sync(B_QK, 384);
                bar_sync(B_RED, 384);
                nslow++;
                if (w == 0 && elect()) {
                    asm volatile("red.release.gpu.global.add.u32 [%0], 1;" :: "l"(&g_flags.slow) : "memory");
                    for (int n = 0;; n++) {
                        uint32_t v; asm volatile("ld.acquire.gpu.global.u32 %0, [%1];" : "=r"(v) : "l"(&g_flags.slow) : "memory");
                        if (v >= 96u * nslow) break;
                        if (n > (1 << 23)) __trap();
                    }
                }
                bar_sync(B_AUX, 128);
                mx = 0;
#pragma unroll 1
                for (int i = 0; i < 10; i++) {
                    float4 a = make_float4(0, 0, 0, 0);
#pragma unroll 4
                    for (int h = 0; h < NH; h++) {
                        const float4 v = __ldcg((const float4*)(g_slow + ((((s & 1) * NH + h) * 20 + w * 5 + (i >> 1)) * 32 + l0) * 8) + (i & 1));
                        a.x += v.x; a.y += v.y; a.z += v.z; a.w += v.w;
                    }
                    const uint32_t o0 = pack2(a.x, a.y), o1 = pack2(a.z, a.w);
                    sts32(sm + C_MEM + (w * 10 + i) * 256 + l0 * 4, o0); sts32(sm + C_MEM + (w * 10 + i) * 256 + 128 + l0 * 4, o1);
                    mx = absmax2(absmax2(mx, o0), o1);
                }
                sts32(sm + C_SCL, 0x3f800000u);
                ex = 0; chk = false;
                bar_sync(B_MEM, 384);
            }
            if (s + 1 == NSEG) {
                bar_sync(B_QK, 384);
                bar_sync(B_VP, 384);
                const float4 y0 = lds128f(lq + C_VP + w * 512), y1 = lds128f(lq + C_VP + w * 512 + 2048);
                sts32(sm + C_VM + w * 256 + l0 * 4, pack2(y0.x + y1.x, y0.y + y1.y)); sts32(sm + C_VM + w * 256 + 128 + l0 * 4, pack2(y0.z + y1.z, y0.w + y1.w));
                bar_arrive(B_OWN, 384);
                break;
            }
            if (w == 3) {
                uint32_t qa[2][4], km[2][4], x, y;
                bar_sync(B_QK, 384);
                ldsm4t(qa[0], qrd); ldsm4t(km[0], lq + C_KM); ldsm4t(qa[1], qrd + 512); ldsm4t(km[1], lq + C_KM + 512);
                SFENCE();
                score_tiles(qa, kb, km, x, y);
                stas1(sc1, x, sm + CB_SC + r1); stas1(sc2, x, sm + CB_SC + r2); stas1(sc1 + 128, y, sm + CB_SC + r1); stas1(sc2 + 128, y, sm + CB_SC + r2);
                sts32(scdst, x); sts32(scdst + 128, y);
            } else {
                uint32_t qa[2][4];
                bar_sync(B_QK, 384);
                ldsm4t(qa[0], qrd); ldsm4t(qa[1], qrd + 512);
                if (w == 0) PROF(6);
                const uint32_t x = score_tile(qa, kb);
                stas1(sc1, x, sm + CB_SC + r1); stas1(sc2, x, sm + CB_SC + r2);
                sts32(scdst, x);
            }
            __syncwarp();
            if (elect()) mbar_arrive(sm + CB_SC);
            SFENCE();
            if (w == 0) PROF(7);
            uint32_t scrd = sm + C_SC + (l0 & 3) * 128 + (((l0 >> 2) ^ (2 * (l0 & 3))) << 4), zrd = sm + C_SC + 512 + ((l0 * 4) ^ 96),
                     od = sm + C_OX + l0 * 8 + w * 256, od1 = od + r1 + 2048, od2 = od + r2 + 1024, vprd = lq + C_VP + w * 512, vmst = sm + C_VM + w * 256 + l0 * 4, ones = 0x3f803f80u, ones2 = 0x3f803f80u, zero = 0;
            PIN(scrd); PIN(zrd); PIN(od); PIN(od1); PIN(od2); PIN(vprd); PIN(vmst); PIN(ones); PIN(ones2); PIN(zero);
            mbar_wait(sm + CB_SC, s & 1);
            float sv[10];
            {
                uint32_t x[3][4], z[3];
#pragma unroll
                for (int p = 0; p < 3; p++) { lds128(x[p], scrd + p * 640); z[p] = lds32(zrd + p * 640); }
                if (w == 1) PROF(8);
#pragma unroll
                for (int i = 0; i < 4; i++) { sv[2 * i] = (lo_f(x[0][i]) + lo_f(x[1][i])) + lo_f(x[2][i]); sv[2 * i + 1] = (hi_f(x[0][i]) + hi_f(x[1][i])) + hi_f(x[2][i]); }
                sv[8] = (lo_f(z[0]) + lo_f(z[1])) + lo_f(z[2]); sv[9] = (hi_f(z[0]) + hi_f(z[1])) + hi_f(z[2]);
            }
            float mxs = fmaxf(fmaxf(fmaxf(sv[0], sv[1]), fmaxf(sv[2], sv[3])), fmaxf(fmaxf(fmaxf(sv[4], sv[5]), fmaxf(sv[6], sv[7])), fmaxf(sv[8], sv[9])));
            {
                const float a = __shfl_xor_sync(0xffffffffu, mxs, 1), b = __shfl_xor_sync(0xffffffffu, mxs, 2), c = __shfl_xor_sync(0xffffffffu, mxs, 3);
                SFENCE();
                bar_sync(B_VP, 384);
                mxs = fmaxf(fmaxf(mxs, a), fmaxf(b, c));
            }
            const float4 y0 = lds128f(vprd), y1 = lds128f(vprd + 2048);
            const uint32_t pm = pack2(ex2(sv[8] - mxs), ex2(sv[9] - mxs));
            uint32_t pa[4];
            pa[0] = pack2(ex2(sv[0] - mxs), ex2(sv[1] - mxs)); pa[2] = pack2(ex2(sv[2] - mxs), ex2(sv[3] - mxs));
            const uint32_t vm0 = pack2(y0.x + y1.x, y0.y + y1.y), vm1 = pack2(y0.z + y1.z, y0.w + y1.w);
            float o[2][4], o2[2][4], sm_[4];
            mma8z(sm_, pm, zero, ones); mma8z(o[0], pm, zero, vm0); mma8z(o[1], pm, zero, vm1);
            sts32(vmst, vm0); sts32(vmst + 128, vm1);
            SFENCE();
            pa[1] = pack2(ex2(sv[4] - mxs), ex2(sv[5] - mxs)); pa[3] = pack2(ex2(sv[6] - mxs), ex2(sv[7] - mxs));
            if (w == 2) PROF(9);
            {
                mma16(sm_, pa, ones, ones2);
                mma16(o[0], pa, vb[0][0], vb[0][1]); mma16z(o2[0], pa, vb[0][2], vb[0][3]);
                mma16(o[1], pa, vb[1][0], vb[1][1]); mma16z(o2[1], pa, vb[1][2], vb[1][3]);
                float inv; asm("rcp.approx.ftz.f32 %0, %1;" : "=f"(inv) : "f"(sm_[0] + sm_[2]));
                const float sc = __int_as_float((127 + ex) << 23);
                const uint32_t a = pack2((o[0][0] + o2[0][2]) * sc * inv, (o[0][1] + o2[0][3]) * sc * inv), b = pack2((o[1][0] + o2[1][2]) * sc * inv, (o[1][1] + o2[1][3]) * sc * inv);
                stas2(od1, a, b, sm + CB_OX + r1); stas2(od2, a, b, sm + CB_OX + r2);
                asm volatile("st.shared.v2.b32 [%0], {%1,%2};" :: "r"(od), "r"(a), "r"(b) : "memory");
                bar_arrive(B_OWN, 384);
                if (w == 0) PROF(10);
            }
            const uint8_t* acc = g_acc + ((s + 1) >> 1) * 32768 + ((s + 1) & 1) * 128 + w * 6400;
            const uint8_t* a4 = acc + (l0 >> 3) * 256 + (l0 & 7) * 16; const uint8_t* a1 = acc + 1024 + l0 * 4;
            PINL(a4); PINL(a1);
            if (w == 1 && elect()) { mbar_expect(sm + CB_SC, 1280); sts32(sm + C_SCL, (127 - ex) << 23); }
            __syncwarp();
            bar_sync(B_RED, 384);
            SFENCE();
            const uint32_t tw = clock();
            SFENCE();
            if (w == 1 && elect()) mbar_expect(sm + CB_OX, 2048);
            __syncwarp();
            { const uint32_t vxrd = lq + l0 * 112 + (((2 * w) ^ vswz(l0)) << 4); mbar_wait(sm + CB_VX, (s + 1) & 1); ldsm4t(vb[0], vxrd + C_VX); ldsm4t(vb[1], (vxrd ^ 16) + C_VX); }
            wait_until(tw + ar.D);
            if (w == 2) PROF(16);
            uint32_t v[5][4], z[5];
            int n = 0;
#pragma unroll
            for (int i = 0; i < 5; i++) {
                asm volatile("ld.relaxed.gpu.global.v4.u32 {%0,%1,%2,%3}, [%4];" : "=r"(v[i][0]), "=r"(v[i][1]), "=r"(v[i][2]), "=r"(v[i][3]) : "l"(a4 + i * 1280) : "memory");
                asm volatile("ld.relaxed.gpu.global.u32 %0, [%1];" : "=r"(z[i]) : "l"(a1 + i * 1280) : "memory");
            }
            while (__any_sync(0xffffffffu, min(min(min(v[0][3], z[0]), min(v[1][3], z[1])), min(min(min(v[2][3], z[2]), min(v[3][3], z[3])), min(v[4][3], z[4]))) < 0x50000000u)) {
#pragma unroll
                for (int i = 0; i < 5; i++) {
                    asm volatile("{ .reg .pred q; setp.lt.u32 q, %3, 0x50000000;\n@q ld.relaxed.gpu.global.v4.u32 {%0,%1,%2,%3}, [%4]; }" : "+r"(v[i][0]), "+r"(v[i][1]), "+r"(v[i][2]), "+r"(v[i][3]) : "l"(a4 + i * 1280) : "memory");
                    asm volatile("{ .reg .pred q; setp.lt.u32 q, %0, 0x50000000;\n@q ld.relaxed.gpu.global.u32 %0, [%1]; }" : "+r"(z[i]) : "l"(a1 + i * 1280) : "memory");
                }
                if (++n > SPIN_LIMIT) __trap();
            }
            if (w == 0) { PROF(11); PROFV(15, n); }
#pragma unroll
            for (int i = 0; i < 5; i++) {
                v[i][0] = h2b(v[i][0]); v[i][1] = h2b(v[i][1]); v[i][2] = h2b(v[i][2]); v[i][3] = h2b_lo(v[i][3], z[i]);
                stsm4(lq + C_MEM + w * 2560 + i * 512, v[i][0], v[i][1], v[i][2], v[i][3]);
            }
            bar_sync(B_MEM, 384);
            SFENCE();
            mx = 0;
#pragma unroll
            for (int i = 0; i < 5; i++) mx = absmax2(absmax2(absmax2(absmax2(mx, v[i][0]), v[i][1]), v[i][2]), v[i][3]);
            chk = true;
        }
    }
}

struct SideMaps { CUtensorMap h, wv, ost, o, wo, slab3, slab2, ln[4], wgate, wup, wdown; };
struct Sched { uint16_t end[64]; uint8_t kind[64], block[64], lsplit[16], slab[16], lnst[16]; };
constexpr int SD_ST = REC, SD_NST = 4, SD_EPI = SD_NST * SD_ST, SD_VEC = SD_EPI + 2 * 24576, SD_BAR = SD_VEC + 6400, SD_SMEM = SD_BAR + 256;
static_assert(SD_SMEM <= 232448, "side shared memory");

template <int NPC, bool V>
__device__ __forceinline__ void tile_out(const float (&acc)[8 * NPC], uint32_t eb, uint32_t efull, uint32_t eempty, int& eph, int w, int lane) {
    const int r = lane & 7, mi = lane >> 3, row = w * 16 + (mi & 1) * 8 + r;
    const uint32_t rb = V ? eb + (row >> 5) * 12288 + (row & 31) * 128 : eb + row * 128, sw = V ? vswz(row & 31) : r;
    mbar_wait(eempty, eph); eph ^= 1;
#pragma unroll
    for (int p = 0; p < NPC; p++) {
        const int oc = 2 * p + (mi >> 1);
        stsm4(rb + (oc >> 3) * (V ? 4096 : 8192) + (((oc & 7) ^ sw) << 4), pack2(acc[8 * p], acc[8 * p + 1]), pack2(acc[8 * p + 2], acc[8 * p + 3]),
              pack2(acc[8 * p + 4], acc[8 * p + 5]), pack2(acc[8 * p + 6], acc[8 * p + 7]));
    }
    PROXY_FENCE();
    __syncwarp();
    if (lane == 0) mbar_arrive(efull);
}

__device__ __forceinline__ void attn_tile(uint32_t base, uint32_t dst, uint32_t eempty, int eph, int mt, int lane) {
    const int r = lane & 7, mi = lane >> 3, g = lane >> 2, t = lane & 3;
    float sc[5][4];
#pragma unroll
    for (int n = 0; n < 5; n++) sc[n][0] = sc[n][1] = sc[n][2] = sc[n][3] = 0.f;
    const uint32_t qrd = base + R_Q + ((mi >> 1) * 8 + r) * 64 + (((2 * mt + (mi & 1)) ^ (r >> 1)) << 4), krd = base + R_K + lane * 64 + ((r >> 1) << 4);
#pragma unroll 2
    for (int k2 = 0; k2 < 6; k2++) {
        const uint32_t cb = (k2 >> 1) * R_J + (k2 & 1) * 2048;
        uint32_t a0[4], a1[4], bb[5][4];
        ldsm4t(a0, qrd + cb); ldsm4t(a1, qrd + cb + 1024);
#pragma unroll
        for (int n = 0; n < 4; n++) ldsm4t(bb[n], (krd ^ (n << 4)) + cb);
        ldsm4t(bb[4], base + R_KM + (k2 >> 1) * R_J + (k2 & 1) * 512 + lane * 16);
#pragma unroll
        for (int n = 0; n < 5; n++) mma16(sc[n], a0, bb[n][0], bb[n][1]);
#pragma unroll
        for (int n = 0; n < 5; n++) mma16(sc[n], a1, bb[n][2], bb[n][3]);
    }
    const float scale = 0.07216878364870322f, l2e = 1.4426950408889634f;
    float v[2][10], mx[2], sum[2];
#pragma unroll
    for (int hf = 0; hf < 2; hf++) {
        mx[hf] = -INFINITY;
#pragma unroll
        for (int n = 0; n < 5; n++) {
            uint32_t u = pack2(sc[n][2 * hf], sc[n][2 * hf + 1]);
            u = pack2(lo_f(u) * scale, hi_f(u) * scale);
            const int lim = 8 * (g >> 1) + 2 * (2 * mt + hf) + (g & 1) - 8 * t - 2 * n;
            v[hf][2 * n] = (n < 4 && lim < 0) ? -1e9f : lo_f(u);
            v[hf][2 * n + 1] = (n < 4 && lim < 1) ? -1e9f : hi_f(u);
            mx[hf] = fmaxf(mx[hf], fmaxf(v[hf][2 * n], v[hf][2 * n + 1]));
        }
    }
#pragma unroll
    for (int o = 1; o < 4; o <<= 1)
#pragma unroll
        for (int hf = 0; hf < 2; hf++) mx[hf] = fmaxf(mx[hf], __shfl_xor_sync(0xffffffffu, mx[hf], o));
#pragma unroll
    for (int hf = 0; hf < 2; hf++) {
        sum[hf] = 0;
#pragma unroll
        for (int q = 0; q < 10; q++) { asm("ex2.approx.ftz.f32 %0, %1;" : "=f"(v[hf][q]) : "f"((v[hf][q] - mx[hf]) * l2e)); sum[hf] += v[hf][q]; }
    }
#pragma unroll
    for (int o = 1; o < 4; o <<= 1)
#pragma unroll
        for (int hf = 0; hf < 2; hf++) sum[hf] += __shfl_xor_sync(0xffffffffu, sum[hf], o);
    uint32_t pa[5][2];
#pragma unroll
    for (int hf = 0; hf < 2; hf++) {
        const float inv = __fdividef(1.f, sum[hf]);
#pragma unroll
        for (int n = 0; n < 5; n++) pa[n][hf] = pack2(v[hf][2 * n] * inv, v[hf][2 * n + 1] * inv);
    }
    mbar_wait(eempty, eph);
    const uint32_t tok = 8 * (r >> 1) + 2 * mi + (r & 1), vrd = base + tok * 128 + (vswz(tok) << 4);
#pragma unroll 2
    for (int n4 = 0; n4 < 6; n4++) {
        const uint32_t c0 = (n4 & 1) * 4;
        uint32_t bm[4], bb[4][4];
        ldsm4(bm, base + R_VM + (n4 >> 1) * R_J + (n4 & 1) * 512 + lane * 16);
#pragma unroll
        for (int u = 0; u < 4; u++) ldsm4t(bb[u], (vrd ^ ((c0 + u) << 4)) + (n4 >> 1) * 4096);
        float o[4][4];
#pragma unroll
        for (int u = 0; u < 4; u++) mma8z(o[u], pa[4][0], pa[4][1], bm[u]);
#pragma unroll
        for (int u = 0; u < 4; u++) mma16(o[u], pa[0][0], pa[0][1], pa[1][0], pa[1][1], bb[u][0], bb[u][1]);
#pragma unroll
        for (int u = 0; u < 4; u++) mma16(o[u], pa[2][0], pa[2][1], pa[3][0], pa[3][1], bb[u][2], bb[u][3]);
#pragma unroll
        for (int p = 0; p < 2; p++)
            stsm4(dst + (n4 >> 1) * 8192 + ((mi & 1) * 8 + r) * 128 + (((c0 + 2 * p + (mi >> 1)) ^ r) << 4), pack2(o[2 * p][0], o[2 * p][1]), pack2(o[2 * p][2], o[2 * p][3]),
                  pack2(o[2 * p + 1][0], o[2 * p + 1][1]), pack2(o[2 * p + 1][2], o[2 * p + 1][3]));
    }
}

#define SPROF(tk, i)
#define TPROF(i)
__device__ __forceinline__ void side_tail(uint32_t wgu, uint32_t wgu_bar, int wgu_ph, uint32_t wd, uint32_t wd_bar, int wd_ph, uint32_t xb, uint32_t gbar, bf16* out, int tid) {
    const int warp = __shfl_sync(0xffffffffu, tid >> 5, 0), lane = tid & 31, r = lane & 7, mi = lane >> 3, blk = blockIdx.x;
    const uint32_t T_GU = xb, T_X = xb + 24576, T_RED = T_X + 10240, T_KEY = T_RED + 8192;
    TPROF(0);
    auto rkey = [](int idx) { uint32_t u = __ldcg((const unsigned short*)g_r + idx); u = (u & 0x8000u) ? (~u & 0xffffu) : (u | 0x8000u); return (u << 16) | (uint32_t)(S_TOK - 1 - idx); };
    {
        if (warp == 0 && lane < 15) flag_wait(&g_flags.ln[lane * 32], 128);
        bar_sync(1, 256);
        uint32_t k[8];
#pragma unroll
        for (int i = 0; i < 8; i++) { const int idx = warp * 240 + i * 32 + lane; k[i] = i * 32 + lane < 240 ? rkey(idx) : 0u; }
#pragma unroll 1
        for (int it = 0; it < 8; it++) {
            const uint32_t m = __reduce_max_sync(0xffffffffu, max(umax3(k[0], k[1], k[2]), max(umax3(k[3], k[4], k[5]), max(k[6], k[7]))));
#pragma unroll
            for (int i = 0; i < 8; i++) if (k[i] == m) k[i] = 0;
            if (lane == 0) sts32(T_KEY + (warp * 8 + it) * 4, m);
        }
    }
    bar_sync(1, 256);
    if (warp == 0) {
        uint32_t k[6];
        k[0] = lds32(T_KEY + lane * 4); k[1] = lds32(T_KEY + 128 + lane * 4);
        if (lane == 0) flag_wait(&g_flags.ln[15 * 32], 128);
        __syncwarp();
        TPROF(1);
#pragma unroll
        for (int i = 0; i < 4; i++) k[2 + i] = rkey(1920 + i * 32 + lane);
#pragma unroll 1
        for (int it = 0; it < 8; it++) {
            const uint32_t m = __reduce_max_sync(0xffffffffu, max(umax3(k[0], k[1], k[2]), umax3(k[3], k[4], k[5])));
#pragma unroll
            for (int i = 0; i < 6; i++) if (k[i] == m) k[i] = 0;
            if (lane == 0) sts32(T_KEY + 256 + it * 4, S_TOK - 1 - (m & 0xffffu));
        }
    }
    bar_sync(1, 256);
    TPROF(2);
    {
        const bf16* src = g_h2 + lds32(T_KEY + 256 + (tid & 7) * 4) * DM + (tid >> 3) * 8;
        uint4 v[3];
#pragma unroll
        for (int i = 0; i < 3; i++) if (i < 2 || tid < 128) v[i] = __ldcg((const uint4*)(src + i * 256));
#pragma unroll
        for (int i = 0; i < 3; i++) if (i < 2 || tid < 128) sts128(T_X + tid * 16 + i * 4096, v[i].x, v[i].y, v[i].z, v[i].w);
    }
    const int trow = lds32(T_KEY + 256 + (lane >> 2) * 4), tcol = (blk < 80 ? blk : 0) * 8 + (lane & 3) * 2;
    const uint32_t fx1 = __ldcg((const uint32_t*)(g_x1 + trow * DM + tcol)), fh2 = __ldcg((const uint32_t*)(g_h2 + trow * DM + tcol)),
                   fgb = __ldcg((const uint32_t*)(g_mod + 5 * DM + tcol));
    const float fr = __uint_as_float((uint32_t)__ldcg((const unsigned short*)g_r + trow) << 16);
    mbar_wait(wgu_bar, wgu_ph);
    bar_sync(1, 256);
    TPROF(3);
    {
        float dg[4] = {0, 0, 0, 0}, du[4] = {0, 0, 0, 0};
#pragma unroll
        for (int k = 0; k < 5; k++) {
            uint32_t b[4], ag[4], au[4];
            ldsm4(b, T_X + (warp * 5 + k) * 256 + (lane & 15) * 16);
            const uint32_t o = ((warp * 5 + k) * 16 + (mi >> 1) * 8 + r) * 32 + (mi & 1) * 16;
            ldsm4t(ag, wgu + o); ldsm4t(au, wgu + 20480 + o);
            mma16(dg, ag, b[0], b[1]); mma16(du, au, b[0], b[1]);
        }
        sts128f(T_RED + warp * 1024 + lane * 16, dg[0], dg[1], dg[2], dg[3]); sts128f(T_RED + warp * 1024 + 512 + lane * 16, du[0], du[1], du[2], du[3]);
    }
    bar_sync(1, 256);
    if (warp == 0) {
        float g4[4] = {0, 0, 0, 0}, u4[4] = {0, 0, 0, 0};
#pragma unroll
        for (int i = 0; i < 8; i++) {
            const float4 a = lds128f(T_RED + i * 1024 + lane * 16), b = lds128f(T_RED + i * 1024 + 512 + lane * 16);
            g4[0] += a.x; g4[1] += a.y; g4[2] += a.z; g4[3] += a.w; u4[0] += b.x; u4[1] += b.y; u4[2] += b.z; u4[3] += b.w;
        }
        float y[4];
#pragma unroll
        for (int i = 0; i < 4; i++) { const float gq = bfr(g4[i]); y[i] = bfr(__fdividef(gq, 1.f + __expf(-gq))) * bfr(u4[i]); }
        g_gu[blk * 64 + lane] = movm_t(pack2(y[0], y[1])); g_gu[blk * 64 + 32 + lane] = movm_t(pack2(y[2], y[3]));
        __syncwarp();
        TPROF(4);
        if (lane == 0) {
            flag_add(&g_flags.gu);
            if (blk < 80) {
                flag_wait(&g_flags.gu, 96);
                mbar_expect(gbar, 24576); bulk_g2s(T_GU, g_gu, 24576, gbar);
            }
        }
        __syncwarp();
    }
    if (blk < 80) {
        mbar_wait(wd_bar, wd_ph);
        mbar_wait(gbar, 0);
        TPROF(5);
        float d[2][4] = {{0, 0, 0, 0}, {0, 0, 0, 0}};
#pragma unroll
        for (int k2 = 0; k2 < 6; k2++) {
            uint32_t b[4]; ldsm4t(b, wd + (warp * 6 + k2) * 512 + lane * 16);
#pragma unroll
            for (int h = 0; h < 2; h++) {
                uint32_t a[4]; ldsm4(a, T_GU + ((warp * 12 + k2 * 2 + h) * 2 + (mi >> 1)) * 128 + r * 16);
                mma16(d[h], a, b[2 * h], b[2 * h + 1]);
            }
        }
        asm volatile("st.shared.v2.f32 [%0], {%1,%2};" :: "r"(T_X + warp * 256 + lane * 8), "f"(d[0][0] + d[1][0]), "f"(d[0][1] + d[1][1]) : "memory");
        bar_sync(1, 256);
        if (warp == 0) {
            float y0 = 0, y1 = 0;
#pragma unroll
            for (int i = 0; i < 8; i++) { const float2 a = lds64f(T_X + i * 256 + lane * 8); y0 += a.x; y1 += a.y; }
            const float sg = bfr(__fdividef(1.f, 1.f + __expf(-fr)));
            const float b0 = bfr(lo_f(fh2) + bfr(bfr(y0) * sg)), b1 = bfr(hi_f(fh2) + bfr(bfr(y1) * sg));
            *(uint32_t*)(out + trow * DM + tcol) = pack2(lo_f(fx1) + bfr(lo_f(fgb) * b0), hi_f(fx1) + bfr(hi_f(fgb) * b1));
        }
    }
    TPROF(6);
}

__global__ void __launch_bounds__(384, 1) k_side(const __grid_constant__ SideMaps mp, const __grid_constant__ Sched sd, const bf16* __restrict__ x,
                                                 const bf16* __restrict__ wr, bf16* __restrict__ out) {
    extern __shared__ __align__(1024) uint8_t smraw[];
    const uint32_t sm = smem_u32(smraw);
    if (sm & 1023) __trap();
    const uint32_t FULL = sm + SD_BAR, EMPTY = FULL + 32, EFULL = FULL + 64, EEMPTY = FULL + 80, IFULL = FULL + 96, IEMPTY = FULL + 128, IQ = FULL + 160,
                   VEC = FULL + 176, GBAR = FULL + 184, LNDONE = FULL + 192, LNFREE = FULL + 200;
    const int tid = threadIdx.x, warp = __shfl_sync(0xffffffffu, tid >> 5, 0), lane = tid & 31;
    const uint64_t ef = policy_stream();
    if (tid == 0) {
        for (int i = 0; i < SD_NST; i++) { mbar_init(FULL + 8 * i, 1); mbar_init(EMPTY + 8 * i, 8); }
        for (int i = 0; i < 2; i++) { mbar_init(EFULL + 8 * i, 4); mbar_init(EEMPTY + 8 * i, 1); }
        for (int i = 0; i < 4; i++) { mbar_init(IFULL + 8 * i, 1); mbar_init(IEMPTY + 8 * i, 11); }
        mbar_init(VEC, 1); mbar_init(GBAR, 1); mbar_init(LNDONE, 8); mbar_init(LNFREE, 1);
        asm volatile("fence.mbarrier_init.release.cluster;" ::: "memory");
    }
    __syncthreads();
    if (warp >= 8) {
      asm volatile("setmaxnreg.dec.sync.aligned.u32 40;");
      if (warp == 8) {
        auto claim = []() { uint32_t v = 0; if (elect()) asm volatile("atom.relaxed.gpu.global.add.u32 %0, [%1], 1;" : "=r"(v) : "l"(&g_flags.next) : "memory"); return v; };
        flag_wait(&g_flags.h, 160);
        uint32_t nxt = claim();
        if (elect()) {
            flags_release();
            mbar_expect(VEC, 6400); bulk_g2s(sm + SD_VEC, g_mod + 2 * DM, 5120, VEC); bulk_g2s(sm + SD_VEC + 5120, wr, 1280, VEC);
        }
        int st = 0, ph = 1, run = 0;
        for (int q = 0;; q++) {
            const int tk = __reduce_max_sync(0xffffffffu, nxt);
            while (run < 64 && tk >= sd.end[run]) run++;
            const int kind = run < 64 ? sd.kind[run] : 4, b = sd.block[run & 63], i = tk - (run ? sd.end[run - 1] : 0), ls = sd.lsplit[b];
            mbar_wait(IEMPTY + 8 * (q & 3), ((q >> 2) & 1) ^ 1);
            if (elect()) {
                sts32(IQ + 4 * (q & 3), kind << 12 | b << 8 | (i & 255));
                mbar_arrive(IFULL + 8 * (q & 3));
            }
            const int nst = kind == 0 ? 10 : kind == 1 ? 4 : kind == 2 ? 192 >> ls : kind == 3 ? sd.lnst[b] : blockIdx.x < 80 ? 2 : blockIdx.x < 96 ? 1 : 0;
            const int kclaim = kind == 4 ? -1 : nst - (kind == 0 || kind == 2 ? 2 : 1);
            if (kind == 1 && elect())
                asm volatile("cp.async.bulk.prefetch.L2.global [%0], 5120;" :: "l"(x + (b * 128 + i * 4) * DM) : "memory");
            if (kind == 3) flag_wait(&g_flags.o[b * 32], 4u << ls);
            for (int kb = 0; kb < nst; kb++) {
                mbar_wait(EMPTY + 8 * st, ph);
                const uint32_t base = sm + st * SD_ST, fb = FULL + 8 * st;
                if (kb == kclaim) nxt = claim();
                if (kind == 0) {
                    if (elect()) {
                        mbar_expect(fb, 40960);
                        tma2d(base, &mp.h, kb * 64, b * 128, fb);
                        tma3d(base + 16384, &mp.wv, kb * 64, i * 3, fb);
                    }
                } else if (kind == 1) {
                    flag_wait(&g_flags.seg[(b * 4 + kb) * 32 + i], 3);
                    if (elect()) { mbar_expect(fb, REC); bulk_g2s_ef(base, g_rec + (size_t)((b * 4 + kb) * NH + i) * REC, REC, fb, ef); }
                } else if (kind == 2) {
                    const int k0 = ((i >> 1) * nst + kb) * 32;
                    if (elect()) { mbar_expect(fb, 28672); tma3d(base + 8192, &mp.wo, k0, (i & 1) * 5, fb); }
                    if (kb == 0) { if (lane < (32 >> ls)) flag_wait(&g_flags.at[b * 32 + (i >> 1) * (32 >> ls) + lane], 2); __syncwarp(); }
                    if (elect()) tma2d(base, &mp.o, k0, b * 128, fb);
                } else if (kind == 3) {
                    if (elect()) {
                        mbar_expect(fb, 40960);
                        asm volatile("cp.async.bulk.tensor.4d.shared::cluster.global.mbarrier::complete_tx::bytes.L2::cache_hint [%0], [%1, {0, 0, %3, %4}], [%2], %5;"
                            :: "r"(base), "l"((uint64_t)&mp.ln[ls - 2]), "r"(fb), "r"((i * nst + kb) * (32 >> ls)), "r"((int)sd.slab[b]), "l"(ef) : "memory");
                    }
                } else if (elect()) {
                    if (kb == 0) {
                        mbar_expect(fb, 40960);
#pragma unroll 1
                        for (int c = 0; c < 5; c++) { tma2d(base + c * 4096, &mp.wgate, blockIdx.x * 16, c * 128, fb); tma2d(base + 20480 + c * 4096, &mp.wup, blockIdx.x * 16, c * 128, fb); }
                    } else {
                        mbar_expect(fb, 24576);
#pragma unroll 1
                        for (int c = 0; c < 6; c++) tma2d(base + c * 4096, &mp.wdown, blockIdx.x * 8, c * 256, fb);
                    }
                }
                __syncwarp();
                if (++st == SD_NST) { st = 0; ph ^= 1; }
            }
            if (kind == 4) break;
        }
      } else {
        if (lane == 0) {
            const int wg = warp - 9; int ph = 0;
            for (int q = 0;; q++) {
                mbar_wait(IFULL + 8 * (q & 3), (q >> 2) & 1);
                const int it = lds32(IQ + 4 * (q & 3));
                mbar_arrive(IEMPTY + 8 * (q & 3));
                const int kind = (it >> 12) & 7, b = (it >> 8) & 15, i = it & 255;
                if (kind == 4) break;
                if (wg == 2) {
                    if (kind == 3) {
                        mbar_wait(LNDONE, ph); ph ^= 1;
                        mbar_arrive(LNFREE);
                        flag_add(&g_flags.ln[b * 32], sd.lnst[b] << (5 - sd.lsplit[b]));
                    }
                    continue;
                }
                if (kind == 3) continue;
                for (int rd = 0; rd < (kind == 2 ? 2 : 1); rd++) {
                    mbar_wait(EFULL + 8 * wg, ph); ph ^= 1;
                    const uint32_t src = sm + SD_EPI + wg * 24576;
                    if (kind == 2) tma3d_store(rd ? &mp.slab2 : &mp.slab3, (sd.slab[b] + (i >> 1)) * 128 + wg * 64, (i & 1) * 5 + rd * 3, src, ef, false);
                    else if (kind == 1) tma3d_store(&mp.ost, b * 128 + wg * 64, i * 3, src, ef, false);
                    else {
                        uint8_t* dst = g_rec + (size_t)((b * 4 + wg * 2) * NH + i) * REC;
                        bulk_s2g(dst, src, 12288); bulk_s2g(dst + NH * REC, src + 12288, 12288);
                    }
                    BULK_COMMIT();
                    BULK_WAIT_READ();
                    mbar_arrive(EEMPTY + 8 * wg);
                }
                BULK_WAIT();
                bump(kind == 0 ? &g_flags.v[b * 32 + i] : kind == 1 ? &g_flags.at[b * 32 + i] : &g_flags.o[b * 32]);
            }
        }
      }
    } else {
        asm volatile("setmaxnreg.inc.sync.aligned.u32 232;");
        const int wg = warp >> 2, w = warp & 3;
        int st = 0, ph = 0, eph = 1, lph = 1;
        const uint32_t eb = sm + SD_EPI + wg * 24576;
        for (int q = 0;; q++) {
            mbar_wait(IFULL + 8 * (q & 3), (q >> 2) & 1);
            const int itc = lds32(IQ + 4 * (q & 3));
            __syncwarp();
            if (lane == 0) mbar_arrive(IEMPTY + 8 * (q & 3));
            const int kind = (itc >> 12) & 7, b = (itc >> 8) & 15, i = itc & 255;
            if (kind == 0) {
                float acc[96];
#pragma unroll
                for (int n = 0; n < 96; n++) acc[n] = 0.f;
                int prev = -1;
                for (int kb = 0; kb < 10; kb++) {
                    mbar_wait(FULL + 8 * st, ph);
                    const uint32_t base = sm + st * SD_ST;
                    WG_FENCE();
#pragma unroll
                    for (int ks = 0; ks < 4; ks++)
                        wgmma_ss_n192_tb(acc, mkdesc(base + wg * 8192 + ks * 32, 16, 1024), mkdesc(base + 16384 + ks * 2048, 8192, 1024), (kb | ks) != 0);
                    WG_COMMIT();
                    if (prev >= 0) { WG_WAIT(1); if (lane == 0) mbar_arrive(EMPTY + 8 * prev); }
                    prev = st;
                    if (++st == SD_NST) { st = 0; ph ^= 1; }
                }
                WG_WAIT(0);
                if (lane == 0) mbar_arrive(EMPTY + 8 * prev);
                tile_out<12, true>(acc, eb, EFULL + 8 * wg, EEMPTY + 8 * wg, eph, w, lane);
            } else if (kind == 1) {
                for (int kb = 0; kb < 4; kb++) {
                    mbar_wait(FULL + 8 * st, ph);
                    if (kb == warp >> 1) {
                        attn_tile(sm + st * SD_ST, eb + (w * 16) * 128, EEMPTY + 8 * wg, eph, warp & 1, lane);
                        eph ^= 1;
                        PROXY_FENCE();
                        __syncwarp();
                        if (lane == 0) mbar_arrive(EFULL + 8 * wg);
                    }
                    if (lane == 0) mbar_arrive(EMPTY + 8 * st);
                    if (++st == SD_NST) { st = 0; ph ^= 1; }
                }
            } else if (kind == 2) {
                float acc[96], acc2[64];
#pragma unroll
                for (int n = 0; n < 96; n++) acc[n] = 0.f;
#pragma unroll
                for (int n = 0; n < 64; n++) acc2[n] = 0.f;
                int prev = -1;
                for (int kb = 192 >> sd.lsplit[b]; kb > 0; kb--) {
                    const uint32_t base = sm + st * SD_ST;
                    mbar_wait(FULL + 8 * st, ph);
                    WG_FENCE();
#pragma unroll
                    for (int ks = 0; ks < 2; ks++) {
                        const uint64_t da = (mkdesc(base + wg * 4096 + ks * 32, 16, 512) & ~(3ull << 62)) | (2ull << 62);
                        wgmma_ss_n192_tb(acc, da, mkdesc(base + 8192 + ks * 2048, 4096, 1024), 1);
                        wgmma_ss_n128_tb(acc2, da, mkdesc(base + 8192 + 3 * 4096 + ks * 2048, 4096, 1024), 1);
                    }
                    WG_COMMIT();
                    if (prev >= 0) { WG_WAIT(1); if (lane == 0) mbar_arrive(EMPTY + 8 * prev); }
                    prev = st;
                    if (++st == SD_NST) { st = 0; ph ^= 1; }
                }
                WG_WAIT(0);
                if (lane == 0) mbar_arrive(EMPTY + 8 * prev);
                tile_out<12, false>(acc, eb, EFULL + 8 * wg, EEMPTY + 8 * wg, eph, w, lane);
                tile_out<8, false>(acc2, eb, EFULL + 8 * wg, EEMPTY + 8 * wg, eph, w, lane);
            } else if (kind == 3) {
                const int ls = sd.lsplit[b], nst = sd.lnst[b], rs = 5 - ls;
                for (int kb = 0; kb < nst; kb++) {
                    const int sst = st, sph = ph;
                    if (++st == SD_NST) { st = 0; ph ^= 1; }
                    if ((warp >> rs) != (kb & ((8 >> rs) - 1))) {
                        mbar_wait(FULL + 8 * sst, sph);
                        if (lane == 0) mbar_arrive(EMPTY + 8 * sst);
                        continue;
                    }
                    const int lr = warp & ((1 << rs) - 1), pos = ((i * nst + kb) << rs) + lr, row = b * 128 + (pos & 96) + 8 * ((pos & 7) >> 1) + 2 * ((pos >> 3) & 3) + (pos & 1);
                    uint2 xin[5];
#pragma unroll
                    for (int q2 = 0; q2 < 5; q2++) xin[q2] = ld_ef(x + row * DM + lane * 4 + q2 * 128, ef);
                    float xv[20], hv[20];
#pragma unroll
                    for (int n = 0; n < 20; n++) xv[n] = 0.f;
                    mbar_wait(VEC, 0);
                    mbar_wait(FULL + 8 * sst, sph);
                    uint32_t src = sm + sst * SD_ST + lr * 1280 + lane * 8;
#pragma unroll 1
                    for (int k = 0; k < (1 << ls); k += 4) {
                        uint32_t z[4][5][2];
#pragma unroll
                        for (int u = 0; u < 4; u++) {
#pragma unroll
                            for (int q2 = 0; q2 < 5; q2++) lds64(z[u][q2], src + q2 * 256);
                            src += 1280 << rs;
                        }
#pragma unroll
                        for (int u = 0; u < 4; u++)
#pragma unroll
                            for (int q2 = 0; q2 < 5; q2++) { xv[4 * q2] += lo_f(z[u][q2][0]); xv[4 * q2 + 1] += hi_f(z[u][q2][0]); xv[4 * q2 + 2] += lo_f(z[u][q2][1]); xv[4 * q2 + 3] += hi_f(z[u][q2][1]); }
                    }
                    __syncwarp();
                    if (lane == 0) mbar_arrive(EMPTY + 8 * sst);
                    const uint32_t vec = sm + SD_VEC + lane * 8;
                    uint32_t sv[10], tv[10];
#pragma unroll
                    for (int q2 = 0; q2 < 5; q2++) {
                        uint32_t ga[2], sh[2], sc[2];
                        lds64(ga, vec + q2 * 256); lds64(sh, vec + 1280 + q2 * 256); lds64(sc, vec + 2560 + q2 * 256);
#pragma unroll
                        for (int e = 0; e < 2; e++) {
                            const int n = 2 * q2 + e; const uint32_t xi = e ? xin[q2].y : xin[q2].x;
                            xv[2 * n] = bfr(lo_f(xi) + bfr(lo_f(ga[e]) * bfr(xv[2 * n]))); xv[2 * n + 1] = bfr(hi_f(xi) + bfr(hi_f(ga[e]) * bfr(xv[2 * n + 1])));
                            sv[n] = sc[e]; tv[n] = sh[e];
                        }
                    }
                    ln_mod(xv, sv, tv, hv);
                    float rsum = 0;
#pragma unroll
                    for (int q2 = 0; q2 < 5; q2++) {
                        const int c = row * DM + lane * 4 + q2 * 128;
                        const float* xx = xv + 4 * q2; const float* hh = hv + 4 * q2;
                        uint32_t gb[2], wv[2]; lds64(gb, vec + 3840 + q2 * 256); lds64(wv, vec + 5120 + q2 * 256);
                        rsum += (hh[0] * lo_f(wv[0]) + hh[1] * hi_f(wv[0])) + (hh[2] * lo_f(wv[1]) + hh[3] * hi_f(wv[1]));
                        st_ef(g_x1 + c, make_uint2(pack2(xx[0], xx[1]), pack2(xx[2], xx[3])), ef);
                        st_ef(g_h2 + c, make_uint2(pack2(hh[0], hh[1]), pack2(hh[2], hh[3])), ef);
                        st_ef(out + c, make_uint2(pack2(xx[0] + bfr(lo_f(gb[0]) * hh[0]), xx[1] + bfr(hi_f(gb[0]) * hh[1])),
                                                  pack2(xx[2] + bfr(lo_f(gb[1]) * hh[2]), xx[3] + bfr(hi_f(gb[1]) * hh[3]))), ef);
                    }
                    rsum = warp_sum(rsum);
                    if (lane == 0) g_r[row] = __float2bfloat16_rn(rsum);
                }
                __syncwarp();
                mbar_wait(LNFREE, lph); lph ^= 1;
                if (lane == 0) mbar_arrive(LNDONE);
            } else {
                if (blockIdx.x < 96) {
                    mbar_wait(EEMPTY + 8 * wg, eph);
                    int s1 = st + 1, p1 = ph; if (s1 == SD_NST) { s1 = 0; p1 ^= 1; }
                    side_tail(sm + st * SD_ST, FULL + 8 * st, ph, sm + s1 * SD_ST, FULL + 8 * s1, p1, sm + SD_EPI, GBAR, out, tid);
                }
                break;
            }
        }
    }
    __syncwarp();
    asm volatile("griddepcontrol.wait;" ::: "memory");
}

typedef CUresult (*EncodeFn)(CUtensorMap*, CUtensorMapDataType, cuuint32_t, void*, const cuuint64_t*, const cuuint64_t*, const cuuint32_t*, const cuuint32_t*,
                             CUtensorMapInterleave, CUtensorMapSwizzle, CUtensorMapL2promotion, CUtensorMapFloatOOBfill);
static EncodeFn s_encode = nullptr;
static void make_map(CUtensorMap* m, const void* p, int rows, int cols, int box_rows, int box_cols = 64) {
    cuuint64_t dims[2] = {(cuuint64_t)cols, (cuuint64_t)rows}, strides[1] = {(cuuint64_t)cols * 2};
    cuuint32_t box[2] = {(cuuint32_t)box_cols, (cuuint32_t)box_rows}, es[2] = {1, 1};
    s_encode(m, CU_TENSOR_MAP_DATA_TYPE_BFLOAT16, 2, (void*)p, dims, strides, box, es, CU_TENSOR_MAP_INTERLEAVE_NONE,
             box_cols == 64 ? CU_TENSOR_MAP_SWIZZLE_128B : box_cols == 32 ? CU_TENSOR_MAP_SWIZZLE_64B : CU_TENSOR_MAP_SWIZZLE_NONE, CU_TENSOR_MAP_L2_PROMOTION_L2_256B, CU_TENSOR_MAP_FLOAT_OOB_FILL_NONE);
}
static void make_map3(CUtensorMap* m, const void* p, int rows, int cols, int box_rows, int box_chunks) {
    cuuint64_t dims[3] = {64, (cuuint64_t)rows, (cuuint64_t)cols / 64}, strides[2] = {(cuuint64_t)cols * 2, 128};
    cuuint32_t box[3] = {64, (cuuint32_t)box_rows, (cuuint32_t)box_chunks}, es[3] = {1, 1, 1};
    s_encode(m, CU_TENSOR_MAP_DATA_TYPE_BFLOAT16, 3, (void*)p, dims, strides, box, es, CU_TENSOR_MAP_INTERLEAVE_NONE,
             CU_TENSOR_MAP_SWIZZLE_128B, CU_TENSOR_MAP_L2_PROMOTION_L2_256B, CU_TENSOR_MAP_FLOAT_OOB_FILL_NONE);
}
template <typename T> static void* sym(T& s) { void* p = nullptr; cudaGetSymbolAddress(&p, s); return p; }

static void make_map_ln(CUtensorMap* m, const void* p, int ls) {
    cuuint64_t dims[4] = {128, 5, 128, NSLAB}, strides[3] = {256, DM * 2, 128 * DM * 2};
    cuuint32_t box[4] = {128, 5, (cuuint32_t)(32 >> ls), (cuuint32_t)(1 << ls)}, es[4] = {1, 1, 1, 1};
    s_encode(m, CU_TENSOR_MAP_DATA_TYPE_BFLOAT16, 4, (void*)p, dims, strides, box, es, CU_TENSOR_MAP_INTERLEAVE_NONE,
             CU_TENSOR_MAP_SWIZZLE_NONE, CU_TENSOR_MAP_L2_PROMOTION_L2_256B, CU_TENSOR_MAP_FLOAT_OOB_FILL_NONE);
}
static void make_sched(Sched* sd, const char* order, const char* lsplit, const char* lnst) {
    int slab = 0, end = 0;
    for (int b = 0; b < 16; b++) { sd->lsplit[b] = lsplit[b] - '0'; sd->lnst[b] = lnst[b] - '0'; sd->slab[b] = slab; slab += 1 << sd->lsplit[b]; }
    for (int r = 0; r < 64; r++) {
        const char k = order[2 * r], c = order[2 * r + 1]; const int b = c <= '9' ? c - '0' : c - 'a' + 10;
        sd->kind[r] = k == 'V' ? 0 : k == 'A' ? 1 : k == 'O' ? 2 : 3; sd->block[r] = b;
        end += k == 'O' ? 2 << sd->lsplit[b] : k == 'L' ? (4 << sd->lsplit[b]) / sd->lnst[b] : 32;
        sd->end[r] = end;
    }
}

extern "C" void kernel_launch(void* const* d_in, const int* in_sizes, int n_in, void* d_out, int out_size) {
    const bf16 *x = (const bf16*)d_in[0], *mem0 = (const bf16*)d_in[1], *Wq = (const bf16*)d_in[2], *Wk = (const bf16*)d_in[3],
               *Wv = (const bf16*)d_in[4], *Wo = (const bf16*)d_in[5], *wr = (const bf16*)d_in[8], *wgate = (const bf16*)d_in[9],
               *wup = (const bf16*)d_in[10], *wdown = (const bf16*)d_in[11], *c = (const bf16*)d_in[12], *wmod = (const bf16*)d_in[13];
    bf16* out = (bf16*)d_out;
    if (!s_encode) {
        cudaDriverEntryPointQueryResult qr;
        cudaGetDriverEntryPoint("cuTensorMapEncodeTiled", (void**)&s_encode, cudaEnableDefault, &qr);
        cudaFuncSetAttribute(k_side, cudaFuncAttributeMaxDynamicSharedMemorySize, SD_SMEM);
        cudaFuncSetAttribute(k_chain, cudaFuncAttributeMaxDynamicSharedMemorySize, C_SMEM);
    }
    ChainMaps cm; SideMaps sd; Sched sc;
    make_map(&sd.h, sym(g_h), S_TOK, DM, 128); make_map3(&sd.wv, Wv, DM, HD, 64, 3);
    make_map3(&sd.ost, sym(g_o), S_TOK, HD, 64, 3); make_map(&sd.o, sym(g_o), S_TOK, HD, 128, 32); make_map3(&sd.wo, Wo, HD, DM, 32, 5);
    make_map3(&sd.slab3, sym(g_slab), NSLAB * 128, DM, 64, 3); make_map3(&sd.slab2, sym(g_slab), NSLAB * 128, DM, 64, 2);
    for (int i = 0; i < 4; i++) make_map_ln(&sd.ln[i], sym(g_slab), i + 2);
    make_map(&sd.wgate, wgate, DM, FF, 128, 16); make_map(&sd.wup, wup, DM, FF, 128, 16); make_map(&sd.wdown, wdown, FF, DM, 256, 8);
    make_map(&cm.wq, Wq, DM, HD, 64); make_map(&cm.wk, Wk, DM, HD, 64); make_map(&cm.wv, Wv, DM, HD, 64); make_map(&cm.wo, Wo, HD, DM, 64, 32);
    make_map3(&cm.h1, sym(g_h), S_TOK, DM, 32, 1); make_map3(&cm.h4, sym(g_h), S_TOK, DM, 32, 4);
    make_map(&cm.wmod, wmod, DM, 6 * DM, 160, 48);
    ChainArgs ar = {x, mem0, c, Wv, Wo, 550, 0};
    const char *order = "V0V1V2V3V4A0V5O0A1V6O1A2V7O2L0A3V8O3L1A4V9O4L2A5VaO5L3A6VbO6L4A7VcO7L5A8VdO8L6A9VeO9L7AaVfOaL8AbL9AcObLaAdOcAeLbOdAfLcOeOfLdLeLf",
               *lsplit = "2222222222333445", *lnst = "2222222222222221";
    make_sched(&sc, order, lsplit, lnst);
    k_chain<<<96, 384, C_SMEM>>>(cm, ar);
    cudaLaunchConfig_t cfg = {};
    cfg.gridDim = dim3(N_SIDE); cfg.blockDim = dim3(384); cfg.dynamicSmemBytes = SD_SMEM; cfg.stream = cudaStreamPerThread;
    cudaLaunchAttribute at[1]; at[0].id = cudaLaunchAttributeProgrammaticStreamSerialization; at[0].val.programmaticStreamSerializationAllowed = 1;
    cfg.attrs = at; cfg.numAttrs = 1;
    cudaLaunchKernelEx(&cfg, k_side, sd, sc, x, wr, out);
}
```

```cpp
#include <cuda_runtime.h>
#include <cuda_bf16.h>
#include <cuda.h>
#include <stdint.h>
#include <stdio.h>
#include <string.h>
#include <stdlib.h>

typedef __nv_bfloat16 bf16;
constexpr int S_TOK = 2048, DM = 640, NH = 32, DH = 192, HD = NH * DH, NSEG = 64, SEG = 32, FF = 1536;

__device__ bf16 g_mod[6 * DM];
__device__ bf16 g_h[S_TOK * DM];
constexpr int REC = 43008, R_Q = 12288, R_K = R_Q + 4096, R_KM = R_Q + 8192, R_VM = R_Q + 9216, R_J = 10240;
__device__ __align__(1024) uint8_t g_rec[(size_t)NSEG * NH * REC];
__host__ __device__ constexpr uint32_t vswz(uint32_t t) { return (t ^ (t >> 3 << 1)) & 7; }
__device__ bf16 g_o[S_TOK * HD];
__device__ bf16 g_x1[S_TOK * DM];
__device__ bf16 g_h2[S_TOK * DM];
__device__ bf16 g_r[S_TOK];
__device__ __align__(128) uint32_t g_gu[FF / 8 * 32];
__device__ __align__(1024) uint8_t g_acc[32 * 32768];
__device__ float g_slow[2 * NH * 20 * 32 * 8];
constexpr int NSLAB = 160;
__device__ bf16 g_slab[NSLAB * 128 * DM];
struct __align__(128) Flags {
    uint32_t v[16 * 32];
    uint32_t seg[64 * 32];
    uint32_t at[16 * 32];
    uint32_t o[16 * 32];
    uint32_t ln[16 * 32];
    uint32_t gu, pad1[31], next, pad2[31], slow, pad3[31];
    uint32_t mod, h, pad4[30], done, pad5[31];
};
__device__ Flags g_flags;

__device__ __forceinline__ uint32_t smem_u32(const void* p) { return (uint32_t)__cvta_generic_to_shared(p); }
__device__ __forceinline__ uint32_t pack2(float lo, float hi) {
    uint32_t r; asm("cvt.rn.bf16x2.f32 %0, %1, %2;" : "=r"(r) : "f"(hi), "f"(lo)); return r;
}
__device__ __forceinline__ float bfr(float x) { return __uint_as_float(pack2(0.f, x)); }
__device__ __forceinline__ float inv_std(float var) {
    float s, r; asm("sqrt.approx.f32 %0, %1;" : "=f"(s) : "f"(bfr(bfr(var) + 1e-5f))); asm("rcp.approx.f32 %0, %1;" : "=f"(r) : "f"(bfr(s))); return r;
}
__device__ __forceinline__ float lo_f(uint32_t v) { return __uint_as_float(v << 16); }
__device__ __forceinline__ float hi_f(uint32_t v) { return __uint_as_float(v & 0xffff0000u); }
__device__ __forceinline__ void mbar_init(uint32_t bar, int cnt) { asm volatile("mbarrier.init.shared::cta.b64 [%0], %1;" :: "r"(bar), "r"(cnt) : "memory"); }
__device__ __forceinline__ void mbar_expect(uint32_t bar, int bytes) { asm volatile("mbarrier.arrive.expect_tx.shared::cta.b64 _, [%0], %1;" :: "r"(bar), "r"(bytes) : "memory"); }
__device__ __forceinline__ void mbar_arrive(uint32_t bar) { asm volatile("mbarrier.arrive.shared::cta.b64 _, [%0];" :: "r"(bar) : "memory"); }
constexpr int SPIN_LIMIT = 1 << 18;
__device__ __forceinline__ void mbar_wait(uint32_t bar, uint32_t par) {
    asm volatile("{ .reg .pred p, q; .reg .u32 n; mov.u32 n, 0;\n"
                 "W_%=: mbarrier.try_wait.parity.shared::cta.b64 p, [%0], %1;\n"
                 "@p bra.uni D_%=;\n"
                 "add.u32 n, n, 1; setp.lt.u32 q, n, 0x200000; @q bra.uni W_%=;\n"
                 "trap;\n"
                 "D_%=: }" :: "r"(bar), "r"(par) : "memory");
}
__device__ __forceinline__ void tma2d(uint32_t dst, const CUtensorMap* m, int c0, int c1, uint32_t bar) {
    asm volatile("cp.async.bulk.tensor.2d.shared::cluster.global.mbarrier::complete_tx::bytes [%0], [%1, {%3, %4}], [%2];"
        :: "r"(dst), "l"((uint64_t)m), "r"(bar), "r"(c0), "r"(c1) : "memory");
}
__device__ __forceinline__ uint64_t policy_stream() { uint64_t p; asm("createpolicy.fractional.L2::evict_first.b64 %0, 1.0;" : "=l"(p)); return p; }
__device__ __forceinline__ void tma2d_ef(uint32_t dst, const CUtensorMap* m, int c0, int c1, uint32_t bar, uint64_t pol) {
    asm volatile("cp.async.bulk.tensor.2d.shared::cluster.global.mbarrier::complete_tx::bytes.L2::cache_hint [%0], [%1, {%3, %4}], [%2], %5;"
        :: "r"(dst), "l"((uint64_t)m), "r"(bar), "r"(c0), "r"(c1), "l"(pol) : "memory");
}
__device__ __forceinline__ void tma3d(uint32_t dst, const CUtensorMap* m, int row, int chunk, uint32_t bar) {
    asm volatile("cp.async.bulk.tensor.3d.shared::cluster.global.mbarrier::complete_tx::bytes [%0], [%1, {0, %3, %4}], [%2];"
        :: "r"(dst), "l"((uint64_t)m), "r"(bar), "r"(row), "r"(chunk) : "memory");
}
__device__ __forceinline__ void tma3d_store(const CUtensorMap* m, int row, int chunk, uint32_t src, uint64_t pol, bool hint) {
    if (hint) asm volatile("cp.async.bulk.tensor.3d.global.shared::cta.bulk_group.L2::cache_hint [%0, {0, %2, %3}], [%1], %4;"
        :: "l"((uint64_t)m), "r"(src), "r"(row), "r"(chunk), "l"(pol) : "memory");
    else asm volatile("cp.async.bulk.tensor.3d.global.shared::cta.bulk_group [%0, {0, %2, %3}], [%1];"
        :: "l"((uint64_t)m), "r"(src), "r"(row), "r"(chunk) : "memory");
}
__device__ __forceinline__ bool elect() { uint32_t p; asm volatile("{ .reg .pred e; elect.sync _|e, -1; selp.u32 %0, 1, 0, e; }" : "=r"(p)); return p; }
__device__ __forceinline__ uint2 ld_ef(const void* p, uint64_t pol) {
    uint2 v; asm volatile("ld.relaxed.gpu.global.L2::cache_hint.v2.u32 {%0,%1}, [%2], %3;" : "=r"(v.x), "=r"(v.y) : "l"(p), "l"(pol)); return v;
}
__device__ __forceinline__ void st_ef(void* p, uint2 v, uint64_t pol) {
    asm volatile("st.global.L2::cache_hint.v2.u32 [%0], {%1,%2}, %3;" :: "l"(p), "r"(v.x), "r"(v.y), "l"(pol) : "memory");
}
__device__ __forceinline__ void bulk_g2s(uint32_t dst, const void* src, int bytes, uint32_t bar) {
    asm volatile("cp.async.bulk.shared::cluster.global.mbarrier::complete_tx::bytes [%0], [%1], %2, [%3];" :: "r"(dst), "l"(src), "r"(bytes), "r"(bar) : "memory");
}
__device__ __forceinline__ void bulk_g2s_ef(uint32_t dst, const void* src, int bytes, uint32_t bar, uint64_t pol) {
    asm volatile("cp.async.bulk.shared::cluster.global.mbarrier::complete_tx::bytes.L2::cache_hint [%0], [%1], %2, [%3], %4;" :: "r"(dst), "l"(src), "r"(bytes), "r"(bar), "l"(pol) : "memory");
}
__device__ __forceinline__ void bulk_s2g(void* dst, uint32_t src, int bytes) {
    asm volatile("cp.async.bulk.global.shared::cta.bulk_group [%0], [%1], %2;" :: "l"(dst), "r"(src), "r"(bytes) : "memory");
}
__device__ __forceinline__ void bulk_s2g_ef(void* dst, uint32_t src, int bytes, uint64_t pol) {
    asm volatile("cp.async.bulk.global.shared::cta.bulk_group.L2::cache_hint [%0], [%1], %2, %3;" :: "l"(dst), "r"(src), "r"(bytes), "l"(pol) : "memory");
}
#define EF 31
#define BULK_COMMIT()    asm volatile("cp.async.bulk.commit_group;" ::: "memory")
#define BULK_WAIT_READ() asm volatile("cp.async.bulk.wait_group.read 0;" ::: "memory")
#define BULK_WAIT()      asm volatile("cp.async.bulk.wait_group 0;" ::: "memory")
#define PROXY_FENCE()    asm volatile("fence.proxy.async.shared::cta;" ::: "memory")
__device__ __forceinline__ void ldsm4(uint32_t (&r)[4], uint32_t a) {
    asm volatile("ldmatrix.sync.aligned.m8n8.x4.shared.b16 {%0,%1,%2,%3}, [%4];" : "=r"(r[0]), "=r"(r[1]), "=r"(r[2]), "=r"(r[3]) : "r"(a) : "memory");
}
__device__ __forceinline__ void ldsm4t(uint32_t (&r)[4], uint32_t a) {
    asm volatile("ldmatrix.sync.aligned.m8n8.x4.trans.shared.b16 {%0,%1,%2,%3}, [%4];" : "=r"(r[0]), "=r"(r[1]), "=r"(r[2]), "=r"(r[3]) : "r"(a) : "memory");
}
__device__ __forceinline__ void stsm4(uint32_t a, uint32_t r0, uint32_t r1, uint32_t r2, uint32_t r3) {
    asm volatile("stmatrix.sync.aligned.m8n8.x4.shared.b16 [%0], {%1,%2,%3,%4};" :: "r"(a), "r"(r0), "r"(r1), "r"(r2), "r"(r3) : "memory");
}
__device__ __forceinline__ uint32_t movm_t(uint32_t v) { uint32_t r; asm volatile("movmatrix.sync.aligned.m8n8.trans.b16 %0, %1;" : "=r"(r) : "r"(v)); return r; }
__device__ __forceinline__ void mma16(float (&d)[4], uint32_t a0, uint32_t a1, uint32_t a2, uint32_t a3, uint32_t b0, uint32_t b1) {
    asm volatile("mma.sync.aligned.m16n8k16.row.col.f32.bf16.bf16.f32 {%0,%1,%2,%3}, {%4,%5,%6,%7}, {%8,%9}, {%0,%1,%2,%3};"
        : "+f"(d[0]), "+f"(d[1]), "+f"(d[2]), "+f"(d[3]) : "r"(a0), "r"(a1), "r"(a2), "r"(a3), "r"(b0), "r"(b1));
}
__device__ __forceinline__ void mma16(float (&d)[4], const uint32_t (&a)[4], uint32_t b0, uint32_t b1) { mma16(d, a[0], a[1], a[2], a[3], b0, b1); }
__device__ __forceinline__ void mma16z(float (&d)[4], const uint32_t (&a)[4], uint32_t b0, uint32_t b1) {
    asm volatile("mma.sync.aligned.m16n8k16.row.col.f32.bf16.bf16.f32 {%0,%1,%2,%3}, {%4,%5,%6,%7}, {%8,%9}, {%10,%10,%10,%10};"
        : "=f"(d[0]), "=f"(d[1]), "=f"(d[2]), "=f"(d[3]) : "r"(a[0]), "r"(a[1]), "r"(a[2]), "r"(a[3]), "r"(b0), "r"(b1), "f"(0.f));
}
__device__ __forceinline__ void mma8z(float (&d)[4], uint32_t a0, uint32_t a1, uint32_t b0) {
    asm volatile("mma.sync.aligned.m16n8k8.row.col.f32.bf16.bf16.f32 {%0,%1,%2,%3}, {%4,%5}, {%6}, {%7,%7,%7,%7};"
        : "=f"(d[0]), "=f"(d[1]), "=f"(d[2]), "=f"(d[3]) : "r"(a0), "r"(a1), "r"(b0), "f"(0.f));
}
__device__ __forceinline__ void bar_sync(int id, int n) { asm volatile("bar.sync %0, %1;" :: "r"(id), "r"(n) : "memory"); }
__device__ __forceinline__ void bar_arrive(int id, int n) { asm volatile("bar.arrive %0, %1;" :: "r"(id), "r"(n) : "memory"); }
__device__ __forceinline__ uint64_t mkdesc(uint32_t addr, uint32_t lbo, uint32_t sbo) {
    return (uint64_t)((addr & 0x3FFFF) >> 4) | ((uint64_t)(lbo >> 4) << 16) | ((uint64_t)(sbo >> 4) << 32) | (1ull << 62);
}
#define WG_FENCE()  asm volatile("wgmma.fence.sync.aligned;" ::: "memory")
#define WG_COMMIT() asm volatile("wgmma.commit_group.sync.aligned;" ::: "memory")
#define WG_WAIT(n)  asm volatile("wgmma.wait_group.sync.aligned %0;" :: "n"(n) : "memory")

__device__ __forceinline__ void wgmma_ss_n192_tb(float (&d)[96], uint64_t a, uint64_t b, int acc) {
    asm volatile("{ .reg .pred p; setp.ne.b32 p, %98, 0;\n"
        "wgmma.mma_async.sync.aligned.m64n192k16.f32.bf16.bf16 {%0,%1,%2,%3,%4,%5,%6,%7,%8,%9,%10,%11,%12,%13,%14,%15,%16,%17,%18,%19,%20,%21,%22,%23,%24,%25,%26,%27,%28,%29,%30,%31,%32,%33,%34,%35,%36,%37,%38,%39,%40,%41,%42,%43,%44,%45,%46,%47,%48,%49,%50,%51,%52,%53,%54,%55,%56,%57,%58,%59,%60,%61,%62,%63,%64,%65,%66,%67,%68,%69,%70,%71,%72,%73,%74,%75,%76,%77,%78,%79,%80,%81,%82,%83,%84,%85,%86,%87,%88,%89,%90,%91,%92,%93,%94,%95}, %96, %97, p, 1, 1, 0, 1; }"
        : "+f"(d[0]), "+f"(d[1]), "+f"(d[2]), "+f"(d[3]), "+f"(d[4]), "+f"(d[5]), "+f"(d[6]), "+f"(d[7]), "+f"(d[8]), "+f"(d[9]), "+f"(d[10]), "+f"(d[11]), "+f"(d[12]), "+f"(d[13]), "+f"(d[14]), "+f"(d[15]), "+f"(d[16]), "+f"(d[17]), "+f"(d[18]), "+f"(d[19]), "+f"(d[20]), "+f"(d[21]), "+f"(d[22]), "+f"(d[23]), "+f"(d[24]), "+f"(d[25]), "+f"(d[26]), "+f"(d[27]), "+f"(d[28]), "+f"(d[29]), "+f"(d[30]), "+f"(d[31]), "+f"(d[32]), "+f"(d[33]), "+f"(d[34]), "+f"(d[35]), "+f"(d[36]), "+f"(d[37]), "+f"(d[38]), "+f"(d[39]), "+f"(d[40]), "+f"(d[41]), "+f"(d[42]), "+f"(d[43]), "+f"(d[44]), "+f"(d[45]), "+f"(d[46]), "+f"(d[47]), "+f"(d[48]), "+f"(d[49]), "+f"(d[50]), "+f"(d[51]), "+f"(d[52]), "+f"(d[53]), "+f"(d[54]), "+f"(d[55]), "+f"(d[56]), "+f"(d[57]), "+f"(d[58]), "+f"(d[59]), "+f"(d[60]), "+f"(d[61]), "+f"(d[62]), "+f"(d[63]), "+f"(d[64]), "+f"(d[65]), "+f"(d[66]), "+f"(d[67]), "+f"(d[68]), "+f"(d[69]), "+f"(d[70]), "+f"(d[71]), "+f"(d[72]), "+f"(d[73]), "+f"(d[74]), "+f"(d[75]), "+f"(d[76]), "+f"(d[77]), "+f"(d[78]), "+f"(d[79]), "+f"(d[80]), "+f"(d[81]), "+f"(d[82]), "+f"(d[83]), "+f"(d[84]), "+f"(d[85]), "+f"(d[86]), "+f"(d[87]), "+f"(d[88]), "+f"(d[89]), "+f"(d[90]), "+f"(d[91]), "+f"(d[92]), "+f"(d[93]), "+f"(d[94]), "+f"(d[95])
        : "l"(a), "l"(b), "r"(acc));
}

__device__ __forceinline__ void wgmma_ss_n128_tb(float (&d)[64], uint64_t a, uint64_t b, int acc) {
    asm volatile("{ .reg .pred p; setp.ne.b32 p, %66, 0;\n"
        "wgmma.mma_async.sync.aligned.m64n128k16.f32.bf16.bf16 {%0,%1,%2,%3,%4,%5,%6,%7,%8,%9,%10,%11,%12,%13,%14,%15,%16,%17,%18,%19,%20,%21,%22,%23,%24,%25,%26,%27,%28,%29,%30,%31,%32,%33,%34,%35,%36,%37,%38,%39,%40,%41,%42,%43,%44,%45,%46,%47,%48,%49,%50,%51,%52,%53,%54,%55,%56,%57,%58,%59,%60,%61,%62,%63}, %64, %65, p, 1, 1, 0, 1; }"
        : "+f"(d[0]), "+f"(d[1]), "+f"(d[2]), "+f"(d[3]), "+f"(d[4]), "+f"(d[5]), "+f"(d[6]), "+f"(d[7]), "+f"(d[8]), "+f"(d[9]), "+f"(d[10]), "+f"(d[11]), "+f"(d[12]), "+f"(d[13]), "+f"(d[14]), "+f"(d[15]), "+f"(d[16]), "+f"(d[17]), "+f"(d[18]), "+f"(d[19]), "+f"(d[20]), "+f"(d[21]), "+f"(d[22]), "+f"(d[23]), "+f"(d[24]), "+f"(d[25]), "+f"(d[26]), "+f"(d[27]), "+f"(d[28]), "+f"(d[29]), "+f"(d[30]), "+f"(d[31]), "+f"(d[32]), "+f"(d[33]), "+f"(d[34]), "+f"(d[35]), "+f"(d[36]), "+f"(d[37]), "+f"(d[38]), "+f"(d[39]), "+f"(d[40]), "+f"(d[41]), "+f"(d[42]), "+f"(d[43]), "+f"(d[44]), "+f"(d[45]), "+f"(d[46]), "+f"(d[47]), "+f"(d[48]), "+f"(d[49]), "+f"(d[50]), "+f"(d[51]), "+f"(d[52]), "+f"(d[53]), "+f"(d[54]), "+f"(d[55]), "+f"(d[56]), "+f"(d[57]), "+f"(d[58]), "+f"(d[59]), "+f"(d[60]), "+f"(d[61]), "+f"(d[62]), "+f"(d[63])
        : "l"(a), "l"(b), "r"(acc));
}

__device__ __forceinline__ void wgmma_rs_n32(float (&d)[16], const uint32_t (&a)[4], uint64_t b) {
    asm volatile("wgmma.mma_async.sync.aligned.m64n32k16.f32.bf16.bf16 {%0,%1,%2,%3,%4,%5,%6,%7,%8,%9,%10,%11,%12,%13,%14,%15}, {%16,%17,%18,%19}, %20, 1, 1, 1, 0;"
        : "+f"(d[0]), "+f"(d[1]), "+f"(d[2]), "+f"(d[3]), "+f"(d[4]), "+f"(d[5]), "+f"(d[6]), "+f"(d[7]), "+f"(d[8]), "+f"(d[9]), "+f"(d[10]), "+f"(d[11]), "+f"(d[12]), "+f"(d[13]), "+f"(d[14]), "+f"(d[15])
        : "r"(a[0]), "r"(a[1]), "r"(a[2]), "r"(a[3]), "l"(b));
}
__device__ __forceinline__ uint32_t umax3(uint32_t a, uint32_t b, uint32_t c) { return max(max(a, b), c); }
__device__ __forceinline__ void wait_until(uint32_t t) { while ((int32_t)((uint32_t)clock() - t) < 0) {} }
__device__ __forceinline__ uint32_t gtime() { uint32_t c; asm volatile("mov.u32 %0, %%globaltimer_lo;" : "=r"(c)); return c; }
__device__ __forceinline__ uint32_t opaque(uint32_t v) { uint32_t r; asm volatile("shfl.sync.bfly.b32 %0, %1, 0, 31, -1;" : "=r"(r) : "r"(v)); return r; }
__device__ __forceinline__ uint32_t lds32(uint32_t a) { uint32_t v; asm volatile("ld.shared.u32 %0, [%1];" : "=r"(v) : "r"(a) : "memory"); return v; }
__device__ __forceinline__ void sts32(uint32_t a, uint32_t v) { asm volatile("st.shared.u32 [%0], %1;" :: "r"(a), "r"(v) : "memory"); }
__device__ __forceinline__ void lds64(uint32_t (&v)[2], uint32_t a) { asm volatile("ld.shared.v2.u32 {%0,%1}, [%2];" : "=r"(v[0]), "=r"(v[1]) : "r"(a) : "memory"); }
__device__ __forceinline__ void lds128(uint32_t (&v)[4], uint32_t a) { asm volatile("ld.shared.v4.u32 {%0,%1,%2,%3}, [%4];" : "=r"(v[0]), "=r"(v[1]), "=r"(v[2]), "=r"(v[3]) : "r"(a) : "memory"); }
__device__ __forceinline__ void sts128(uint32_t a, uint32_t x, uint32_t y, uint32_t z, uint32_t w) { asm volatile("st.shared.v4.u32 [%0], {%1,%2,%3,%4};" :: "r"(a), "r"(x), "r"(y), "r"(z), "r"(w) : "memory"); }
__device__ __forceinline__ float2 lds64f(uint32_t a) { float2 v; asm volatile("ld.shared.v2.f32 {%0,%1}, [%2];" : "=f"(v.x), "=f"(v.y) : "r"(a) : "memory"); return v; }
__device__ __forceinline__ float4 lds128f(uint32_t a) { float4 v; asm volatile("ld.shared.v4.f32 {%0,%1,%2,%3}, [%4];" : "=f"(v.x), "=f"(v.y), "=f"(v.z), "=f"(v.w) : "r"(a) : "memory"); return v; }
__device__ __forceinline__ void sts128f(uint32_t a, float x, float y, float z, float w) { asm volatile("st.shared.v4.f32 [%0], {%1,%2,%3,%4};" :: "r"(a), "f"(x), "f"(y), "f"(z), "f"(w) : "memory"); }

__device__ __forceinline__ float warp_sum(float v) {
#pragma unroll
    for (int o = 16; o; o >>= 1) v += __shfl_xor_sync(0xffffffffu, v, o);
    return v;
}
__device__ __forceinline__ uint32_t badd(uint32_t a, uint32_t b) { uint32_t r; asm("add.rn.bf16x2 %0, %1, %2;" : "=r"(r) : "r"(a), "r"(b)); return r; }
__device__ __forceinline__ uint32_t bsub(uint32_t a, uint32_t b) { uint32_t r; asm("sub.rn.bf16x2 %0, %1, %2;" : "=r"(r) : "r"(a), "r"(b)); return r; }
__device__ __forceinline__ uint32_t bmul(uint32_t a, uint32_t b) { uint32_t r; asm("mul.rn.bf16x2 %0, %1, %2;" : "=r"(r) : "r"(a), "r"(b)); return r; }
__device__ __forceinline__ void ln_row(const uint32_t (&x)[10], uint32_t (&n)[10]) {
    float s0 = 0, s1 = 0;
#pragma unroll
    for (int i = 0; i < 10; i++) { s0 += lo_f(x[i]); s1 += hi_f(x[i]); }
    const float mean = warp_sum(s0 + s1) * (1.f / DM);
    float q0 = 0, q1 = 0;
#pragma unroll
    for (int i = 0; i < 10; i++) { const float d0 = lo_f(x[i]) - mean, d1 = hi_f(x[i]) - mean; q0 += d0 * d0; q1 += d1 * d1; }
    const uint32_t mb = pack2(mean, mean);
    const float inv = inv_std(warp_sum(q0 + q1) * (1.f / DM));
#pragma unroll
    for (int i = 0; i < 10; i++) { const uint32_t d = bsub(x[i], mb); n[i] = pack2(lo_f(d) * inv, hi_f(d) * inv); }
}
__device__ __forceinline__ uint32_t ld_rlx(const uint32_t* f) { uint32_t v; asm volatile("ld.relaxed.gpu.global.u32 %0, [%1];" : "=r"(v) : "l"(f) : "memory"); return v; }
__device__ __forceinline__ void bump(uint32_t* f) { asm volatile("red.relaxed.gpu.global.add.u32 [%0], 1;" :: "l"(f) : "memory"); }
__device__ __forceinline__ void flag_wait(const uint32_t* f, uint32_t target) {
    for (int n = 0;; n++) {
        uint32_t v; asm volatile("ld.relaxed.gpu.global.u32 %0, [%1];" : "=r"(v) : "l"(f) : "memory");
        if (v >= target) break;
        if (n > (1 << 23)) __trap();
    }
}
__device__ __forceinline__ void flag_wait_warp(const uint32_t* f, uint32_t target) {
    for (int n = 0; !__all_sync(0xffffffffu, ld_rlx(f) >= target); n++) if (n > (1 << 23)) __trap();
}
__device__ __forceinline__ void flag_add(uint32_t* f, uint32_t v = 1) { asm volatile("red.release.gpu.global.add.u32 [%0], %1;" :: "l"(f), "r"(v) : "memory"); }
constexpr int N_SIDE = 132;
__device__ __forceinline__ void flags_release() {
    uint32_t old; asm volatile("atom.acq_rel.gpu.global.add.u32 %0, [%1], 1;" : "=r"(old) : "l"(&g_flags.done) : "memory");
    if (old == 96 + N_SIDE - 1) { g_flags.mod = 0; g_flags.h = 0; g_flags.done = 0; }
}

struct ChainMaps { CUtensorMap wq, wk, wv, wo, h1, h4, wmod; };
struct ChainArgs { const bf16 *x, *mem0, *c, *wv, *wo; int D, force; };
constexpr uint32_t SM_BASE = 1024;
constexpr int C_WV = 0, C_WO = 81920, C_XR = 167936, C_QX = C_XR + 4 * 4096, C_KX = C_XR + 9 * 4096, C_VX = C_XR + 40960, C_MEM = C_VX + 4096, C_VP = C_MEM,
              C_QM = C_MEM + 10240, C_KM = C_QM + 1024, C_VM = C_KM + 1024, C_OX = C_VM + 1024, C_SC = C_OX + 3072, C_BAR = C_SC + 1920, C_SMEM = C_BAR + 256;
constexpr int CB_W = C_BAR, CB_W2 = C_BAR + 8, CB_SC = C_BAR + 16, CB_OX = C_BAR + 24, CB_VX = C_BAR + 32, CB_XF = C_BAR + 40, CB_XG = C_BAR + 48, CB_PRE = C_BAR + 56,
              C_MAX = C_BAR + 64, C_SCL = C_BAR + 80, C_BAD = C_BAR + 84;
static_assert(C_SMEM <= 232448, "chain shared memory");
enum { B_MEM = 1, B_QK, B_VP, B_OWN, B_RED, B_X, B_AUX, B_VM };
constexpr int NP = 8;
constexpr int NW = 8;
constexpr int BD = 2, VD = 1, OD = 4;
#define PROF(i)
#define PROFG(i)
#define PROFV(i, v)
#define SFENCE() asm volatile("griddepcontrol.launch_dependents;" ::: "memory")
#define PIN(x) asm volatile("" : "+r"(x))
#define PINL(x) asm volatile("" : "+l"(x))
__host__ __device__ constexpr bool pair_v(int i) { return i == 0 || (i % 3 == 2 && i < 9); }
__host__ __device__ constexpr bool pair_own(int i) { return pair_v(i) || i >= 14; }
__host__ __device__ constexpr int pair_idx(int i) { return pair_v(i) ? (i + 1) / 3 : i < 14 ? i - (i < 9 ? i / 3 + 1 : 4) : i - 10; }

__device__ __forceinline__ uint32_t packh(float lo, float hi) { uint32_t r; asm("cvt.rn.f16x2.f32 %0, %1, %2;" : "=r"(r) : "f"(hi), "f"(lo)); return r; }
__device__ __forceinline__ uint32_t h2b(uint32_t v) {
    uint32_t r; asm("{ .reg .f16 a, b; .reg .f32 x, y; mov.b32 {a, b}, %1; cvt.f32.f16 x, a; cvt.f32.f16 y, b; cvt.rn.bf16x2.f32 %0, y, x; }" : "=r"(r) : "r"(v)); return r;
}
__device__ __forceinline__ uint32_t h2b_lo(uint32_t u, uint32_t v) {
    uint32_t r; asm("{ .reg .f16 a, b, c, d; .reg .f32 x, y; mov.b32 {a, b}, %1; mov.b32 {c, d}, %2; cvt.f32.f16 x, a; cvt.f32.f16 y, c; cvt.rn.bf16x2.f32 %0, y, x; }" : "=r"(r) : "r"(u), "r"(v)); return r;
}
constexpr float SCL2E = 0.07216878364870322f * 1.4426950408889634f;
__device__ __forceinline__ uint32_t score_tile(const uint32_t (&qa)[2][4], const uint32_t (&kb)[2][4]) {
    float u[4], v[4], x[4], y[4];
    mma16z(u, qa[0], kb[0][0], kb[0][1]); mma16z(v, qa[0], kb[0][2], kb[0][3]);
    mma16z(x, qa[1], kb[1][0], kb[1][1]); mma16z(y, qa[1], kb[1][2], kb[1][3]);
    return pack2(((u[0] + v[2]) + (x[0] + y[2])) * SCL2E, ((u[1] + v[3]) + (x[1] + y[3])) * SCL2E);
}
__device__ __forceinline__ void score_tiles(const uint32_t (&qa)[2][4], const uint32_t (&kb)[2][4], const uint32_t (&km)[2][4], uint32_t& a, uint32_t& b) {
    float u[4], v[4], x[4], y[4];
    mma16z(u, qa[0], kb[0][0], kb[0][1]); mma16z(v, qa[0], kb[0][2], kb[0][3]); mma16z(x, qa[0], km[0][0], km[0][1]); mma16z(y, qa[0], km[0][2], km[0][3]);
    mma16(u, qa[1], kb[1][0], kb[1][1]); mma16(v, qa[1], kb[1][2], kb[1][3]); mma16(x, qa[1], km[1][0], km[1][1]); mma16(y, qa[1], km[1][2], km[1][3]);
    a = pack2((u[0] + v[2]) * SCL2E, (u[1] + v[3]) * SCL2E); b = pack2((x[0] + y[2]) * SCL2E, (x[1] + y[3]) * SCL2E);
}
__device__ __forceinline__ void stas1(uint32_t dst, uint32_t x, uint32_t bar) {
    asm volatile("st.async.shared::cluster.mbarrier::complete_tx::bytes.b32 [%0], %1, [%2];" :: "r"(dst), "r"(x), "r"(bar) : "memory");
}
__device__ __forceinline__ void stas2(uint32_t dst, uint32_t x, uint32_t y, uint32_t bar) {
    asm volatile("st.async.shared::cluster.mbarrier::complete_tx::bytes.v2.b32 [%0], {%1,%2}, [%3];" :: "r"(dst), "r"(x), "r"(y), "r"(bar) : "memory");
}
__device__ __forceinline__ float ex2(float x) { float r; asm volatile("ex2.approx.ftz.f32 %0, %1;" : "=f"(r) : "f"(x)); return r; }
__device__ __forceinline__ void h_fetch_a(const ChainMaps& mp, uint32_t sm, int n) {
    mbar_expect(sm + CB_XF, 32768);
    tma3d(sm + C_XR, &mp.h4, n * SEG, 0, sm + CB_XF); tma3d(sm + C_XR + 20480, &mp.h4, n * SEG, 5, sm + CB_XF);
}
__device__ __forceinline__ void h_fetch_b(const ChainMaps& mp, uint32_t sm, int n) {
    mbar_expect(sm + CB_XG, 8192);
    tma3d(sm + C_QX, &mp.h1, n * SEG, 4, sm + CB_XG); tma3d(sm + C_KX, &mp.h1, n * SEG, 9, sm + CB_XG);
}
__device__ __forceinline__ uint32_t absmax2(uint32_t a, uint32_t b) {
    uint32_t r; asm("max.u16x2 %0, %1, %2;" : "=r"(r) : "r"(a), "r"(b & 0x7fff7fffu)); return r;
}

__global__ void __cluster_dims__(3, 1, 1) __launch_bounds__(384, 1) k_chain(const __grid_constant__ ChainMaps mp, const __grid_constant__ ChainArgs ar) {
    extern __shared__ __align__(1024) uint8_t smraw[];
    const uint32_t sm = SM_BASE + ((blockIdx.x % 3) << 24);
    if (smem_u32(smraw) != sm) __trap();
    uint32_t tid; asm volatile("mov.u32 %0, %%tid.x;" : "=r"(tid));
    const int warp = __shfl_sync(0xffffffffu, tid >> 5, 0), lane = tid & 31, wg = warp >> 2, w = warp & 3;
    const int blk = blockIdx.x, head = blk / 3, j = blk % 3;
    const int col0 = head * DH + j * 64, u0 = 7 * j, nu = j == 2 ? 6 : 7;
    asm volatile("griddepcontrol.launch_dependents;");
#define PPROF(i)
    PPROF(0);
    {
        const int mc0 = (blk >> 1) * 80 + (blk & 1) * 32, mcn = (blk & 1) ? 24 : 16;
        const int nrow = blk < 74 ? 2 : blk == 74 ? (warp < 8 ? 2 : 1) : 1;
        if (tid == 0) {
            mbar_init(sm + CB_PRE, 1);
            asm volatile("fence.mbarrier_init.release.cluster;" ::: "memory");
            const int n1 = blk < 74 ? 15360 : blk == 74 ? 10240 : 0;
            mbar_expect(sm + CB_PRE, 61440 + 1280 + 15360 + n1);
            bulk_g2s(sm + C_QM, ar.c, 1280, sm + CB_PRE);
#pragma unroll 1
            for (int c = 0; c < 4; c++) tma2d(sm + C_WO + 24576 + c * 15360, &mp.wmod, mc0, c * 160, sm + CB_PRE);
            bulk_g2s(sm + C_XR, ar.x + blk * 12 * DM, 15360, sm + CB_PRE);
            if (n1) bulk_g2s(sm + C_XR + 15360, ar.x + (1152 + blk * 12) * DM, n1, sm + CB_PRE);
        }
        if (tid == 32) {
#pragma unroll 1
            for (int c = 0; c < 7; c++) mbar_init(sm + C_BAR + 8 * c, c == 2 ? 5 : 1);
            asm volatile("fence.mbarrier_init.release.cluster;" ::: "memory");
            mbar_expect(sm + CB_SC, 1280); mbar_expect(sm + CB_OX, 2048);
        }
#pragma unroll 1
        for (int i = blk * 384 + tid; i < 32 * 1600; i += 96 * 384) ((uint4*)g_acc)[i / 1600 * 2048 + i % 1600] = make_uint4(0, 0, 0, 0);
        if (tid < 12 && blk * 12 + tid < (int)(offsetof(Flags, mod) / 16)) ((uint4*)&g_flags)[blk * 12 + tid] = make_uint4(0, 0, 0, 0);
        static_assert(offsetof(Flags, mod) <= 96 * 12 * 16, "flags");
        PPROF(8);
        asm volatile("barrier.cluster.arrive.release.aligned; barrier.cluster.wait.acquire.aligned;" ::: "memory");
        PPROF(9);
        mbar_wait(sm + CB_PRE, 0);
        PPROF(10);
        if (tid == 352) {
            const uint64_t ef = policy_stream();
            mbar_expect(sm + CB_W, 2 * 81920);
#pragma unroll 1
            for (int c = 0; c < 10; c++) tma2d_ef(sm + C_WV + c * 8192, &mp.wq, col0, c * 64, sm + CB_W, ef);
        }
        if (tid < 320) {
            const uint32_t cv = lds32(sm + C_QM + tid * 4);
            asm volatile("st.shared.v2.f32 [%0], {%1,%2};" :: "r"(sm + C_VX + tid * 8), "f"(bfr(__fdividef(lo_f(cv), 1.f + __expf(-lo_f(cv))))),
                         "f"(bfr(__fdividef(hi_f(cv), 1.f + __expf(-hi_f(cv))))) : "memory");
        }
        __syncthreads();
        {
            float a0 = 0, a1 = 0;
            const uint32_t k0 = (tid / 24) * 40, wa0 = sm + C_WO + 24576 + k0 * 96 + (tid % 24) * 4;
#pragma unroll 4
            for (int i = 0; i < 40; i++) {
                const float sc = __uint_as_float(lds32(sm + C_VX + (k0 + i) * 4));
                const uint32_t wv = lds32(wa0 + i * 96);
                a0 += sc * lo_f(wv); a1 += sc * hi_f(wv);
            }
            asm volatile("st.shared.v2.f32 [%0], {%1,%2};" :: "r"(sm + C_MEM + tid * 8), "f"(a0), "f"(a1) : "memory");
        }
        __syncthreads();
        PPROF(11);
        if (warp == 0) {
            float a0 = 0, a1 = 0;
            const int cp = lane < mcn ? lane : 0;
#pragma unroll 4
            for (int i = 0; i < 16; i++) { const float2 v = lds64f(sm + C_MEM + (i * 24 + cp) * 8); a0 += v.x; a1 += v.y; }
            uint32_t* dst = (uint32_t*)(g_mod + mc0) + cp;
            *dst = pack2(a0, a1);
            const uint32_t rb = ld_rlx(dst);
            PPROF(1);
            if (__all_sync(0xffffffffu, rb == pack2(a0, a1)) && tid == 0) bump(blk < 32 ? &g_flags.mod : &g_flags.h);
            if (tid == 0) flag_wait(&g_flags.mod, 32);
            PPROF(2);
        }
        __syncthreads();
        uint32_t sv[10], tv[10], bad = 0;
#pragma unroll
        for (int i = 0; i < 10; i++) { sv[i] = __ldcg((const uint32_t*)g_mod + DM / 2 + lane + 32 * i); tv[i] = __ldcg((const uint32_t*)g_mod + lane + 32 * i); }
#pragma unroll 1
        for (int q = 0; q < nrow; q++) {
            uint32_t xv[10], hv[10];
#pragma unroll
            for (int i = 0; i < 10; i++) xv[i] = lds32(sm + C_XR + q * 15360 + warp * 1280 + lane * 4 + i * 128);
            ln_row(xv, hv);
            uint32_t* dst = (uint32_t*)g_h + (q * 1152 + blk * 12 + warp) * (DM / 2) + lane;
#pragma unroll
            for (int i = 0; i < 10; i++) { hv[i] = badd(bmul(hv[i], badd(sv[i], 0x3f803f80u)), tv[i]); dst[32 * i] = hv[i]; }
#pragma unroll
            for (int i = 0; i < 10; i++) bad |= ld_rlx(dst + 32 * i) ^ hv[i];
        }
        if (__syncthreads_or(bad)) __trap();
        PPROF(3);
        if (tid == 0) {
            bump(&g_flags.h);
            flag_wait(&g_flags.h, 160);
            h_fetch_a(mp, sm, 0); h_fetch_b(mp, sm, 0);
            const uint64_t ef = policy_stream();
#pragma unroll 1
            for (int c = 0; c < 10; c++) tma2d_ef(sm + C_WO + c * 8192, &mp.wk, col0, c * 64, sm + CB_W, ef);
        }
        if (tid == 0) flags_release();
        PPROF(4);
        __syncthreads();
        if (tid >= 64) {
#pragma unroll 1
            for (int i = tid - 64; i < 640 + 192 * 4; i += 320)
                asm volatile("prefetch.global.L2 [%0];" :: "l"(i < 640 ? ar.wv + (size_t)i * HD + col0 : ar.wo + (size_t)(head * DH + ((i - 640) >> 2)) * DM + u0 * 32 + min((i & 3) * 64, 639 - u0 * 32)));
        }
    }
    const int r = lane & 7, mi = lane >> 3;
    uint8_t* const rec0 = g_rec + (size_t)head * REC;
    if (wg < 2) {
        asm volatile("setmaxnreg.inc.sync.aligned.u32 224;");
        const uint32_t l16 = opaque(sm + lane * 16);
        uint32_t wa[40][4], pl[NP][4];
        const uint32_t wfrag = ((mi >> 1) * 8 + r) * 128 + (((2 * w + (mi & 1)) ^ r) << 4);
        mbar_wait(sm + CB_W, 0);
#pragma unroll
        for (int i = 0; i < 40; i++)
            ldsm4t(wa[i], sm + (wg == 0 ? C_WV : C_WO) + wfrag + ((pair_own(i >> 1) ? wg : 1 - wg) * 20 + pair_idx(i >> 1) * 2 + (i & 1)) * 2048);
        PPROF(5);
        bar_arrive(B_OWN, 384);
        mbar_wait(sm + CB_W2, 0);
        PPROF(7);
        const uint32_t wvrd = opaque(sm + C_WV + wfrag + wg * 40960);
        const uint32_t word = opaque(sm + C_WO + warp * 12288 + ((mi >> 1) * 8 + r) * 64 + (((mi & 1) ^ (r >> 1)) << 4));
        const uint32_t own = wg * 5120, oth = 5120 - own;
        mbar_wait(sm + CB_XF, 0);
#pragma unroll 1
        for (int s = -1;;) {
            uint64_t xo = mkdesc(SM_BASE + C_XR + wg * 20480, 16, 1024), xt = mkdesc(SM_BASE + C_XR + 20480 - wg * 20480, 16, 1024);
            if (s >= 0) {
                float dv[2][4], d[4][4], u[4], isc;
                uint32_t b[20][4], l4;
                const uint32_t mo = l16 + C_MEM + own, mt = l16 + C_MEM + oth;
                bar_sync(B_MEM, 384);
#pragma unroll
                for (int i = 0; i < BD; i++) ldsm4t(b[i], (pair_own(i) ? mo : mt) + pair_idx(i) * 512);
                if (warp == 0) { PROF(0); PROFG(24); }
#pragma unroll
                for (int i = 0; i < 20; i++) {
                    const int c = i < 3 ? 0 : (i & 1) * 2, p = 2 * pair_idx(i);
                    SFENCE();
                    if (i + BD < 20) ldsm4t(b[i + BD], (pair_own(i + BD) ? mo : mt) + pair_idx(i + BD) * 512);
                    if (i > 0 && pair_v(i)) { mma16(dv[0], pl[p % NP], b[i][0], b[i][1]); mma16(dv[1], pl[(p + 1) % NP], b[i][2], b[i][3]); }
                    if (i == 0 || i == 3) { mma16z(d[c], wa[2 * i], b[i][0], b[i][1]); mma16z(d[c + 1], wa[2 * i + 1], b[i][2], b[i][3]); }
                    else { mma16(d[c], wa[2 * i], b[i][0], b[i][1]); mma16(d[c + 1], wa[2 * i + 1], b[i][2], b[i][3]); }
                    if (i == 0) { mma16z(dv[0], pl[0], b[i][0], b[i][1]); mma16z(dv[1], pl[1], b[i][2], b[i][3]); }
                    if (i == 12) isc = __uint_as_float(lds32(sm + C_SCL));
                    if (i == 17) { l4 = l16; PIN(l4); l4 = (l4 >> 2) & 127; PIN(l4); }
                }
                SFENCE();
#pragma unroll
                for (int i = 0; i < 4; i++) u[i] = fmaf(d[2][i] + d[3][i], isc, (d[0][i] + d[1][i]) * isc);
                const uint32_t qs = sm + C_QM + warp * 256 + l4;
                sts32(qs, pack2(u[0], u[1])); sts32(qs + 128, pack2(u[2], u[3]));
                if (warp == 2) PROF(1);
                bar_sync(B_QK, 384);
                if (lds32(sm + C_BAD)) {
                    if (warp < nu) {
                        float e[2][4] = {{0, 0, 0, 0}, {0, 0, 0, 0}};
#pragma unroll 1
                        for (int k = 0; k < 12; k++) {
                            uint32_t ob[2]; lds64(ob, sm + C_OX + k * 256 + l4 * 2);
                            ldsm4t(pl[0], word + k * 1024); ldsm4t(pl[1], (word ^ 32) + k * 1024);
                            mma16(e[0], pl[0], ob[0], ob[1]); mma16(e[1], pl[1], ob[0], ob[1]);
                        }
                        float4* dst = (float4*)(g_slow + (((s & 1) * NH + head) * 20 + u0 + warp) * 256 + l4 * 2);
                        dst[0] = make_float4(e[0][0] * isc, e[0][1] * isc, e[0][2] * isc, e[0][3] * isc); dst[1] = make_float4(e[1][0] * isc, e[1][1] * isc, e[1][2] * isc, e[1][3] * isc);
                        __threadfence();
                    }
                    bar_arrive(B_RED, 384);
#pragma unroll
                    for (int i = 0; i < NP; i++) ldsm4t(pl[i], wvrd + i * 2048);
                    continue;
                }
                {
                    uint32_t a[20][4];
#pragma unroll
                    for (int f = NP; f < NP + VD; f++) ldsm4t(a[f], wvrd + f * 2048);
#pragma unroll
                    for (int f = NP; f < 20; f++) {
                        SFENCE();
                        if (f + VD < 20) ldsm4t(a[f + VD], wvrd + (f + VD) * 2048);
                        mma16(dv[f & 1], a[f], b[10 + (f >> 1)][2 * (f & 1)], b[10 + (f >> 1)][2 * (f & 1) + 1]);
                    }
                    sts128f(l16 + C_VP + warp * 512, (dv[0][0] + dv[1][0]) * isc, (dv[0][1] + dv[1][1]) * isc, (dv[0][2] + dv[1][2]) * isc, (dv[0][3] + dv[1][3]) * isc);
                    if (warp == 0) PROF(2);
                }
                if (warp >= nu || s + 1 == NSEG) {
                    if (warp == 7 && elect()) BULK_WAIT();
                    __syncwarp();
                    bar_arrive(B_VP, 384);
                    if (warp == 7) {
                        uint8_t* rec = rec0 + (size_t)s * (NH * REC) + j * R_J;
                        const uint64_t ef = policy_stream();
                        if (elect()) {
                            PROXY_FENCE();
                            bulk_s2g_ef(rec + R_Q, sm + C_QX, 4096, ef); bulk_s2g_ef(rec + R_K, sm + C_KX, 4096, ef); bulk_s2g_ef(rec + R_KM, sm + C_KM, 1024, ef);
                            BULK_COMMIT();
                            if (s > 0) bump(&g_flags.seg[(s - 1) * 32 + head]);
                            if (s + 3 < NSEG) {
                                const uint8_t* ln = g_acc + ((s + 3) >> 1) * 32768 + ((s + 3) & 1) * 128 + blk * 256;
                                asm volatile("prefetch.global.L2 [%0];" :: "l"(ln) : "memory");
                                if (blk < 4) asm volatile("prefetch.global.L2 [%0];" :: "l"(ln + 96 * 256) : "memory");
                            }
                            if (s + 2 < NSEG && blk < 10) asm volatile("cp.async.bulk.prefetch.L2.global [%0], 4096;" :: "l"(g_h + (s + 2) * SEG * DM + blk * 2048) : "memory");
                        }
                        __syncwarp();
                        if ((s & 3) == 2 && s + 2 < NSEG) flag_wait_warp(&g_flags.v[((s + 2) >> 2) * 32 + head], 2);
                        bar_sync(B_VM, 160);
                        if (s + 1 < NSEG) mbar_wait(sm + CB_OX, s & 1);
                        if (elect()) {
                            if (s + 1 < NSEG) { BULK_WAIT_READ(); h_fetch_b(mp, sm, s + 1); }
                            PROXY_FENCE();
                            bulk_s2g_ef(rec + R_VM, sm + C_VM, 1024, ef);
                            BULK_COMMIT();
                            if (s + 1 == NSEG) { BULK_WAIT(); bump(&g_flags.seg[s * 32 + head]); }
                        }
                        __syncwarp();
                    }
                    if (s + 1 == NSEG) break;
                    bar_arrive(B_RED, 384);
                    mbar_wait(sm + CB_XF, (s + 1) & 1);
                } else {
                    uint32_t w1 = word; PIN(w1); w1 ^= 32;
                    auto frag = [&](int f) { return ((f & 1) ? w1 : word) + (f >> 1) * 1024; };
                    uint32_t a[24][4];
                    bar_arrive(B_VP, 384);
                    uint8_t* acc = g_acc + ((s + 1) >> 1) * 32768 + ((s + 1) & 1) * 128 + (u0 + warp) * 1280;
                    uint32_t ln = l16; PIN(ln); ln = ln >> 4 & 31;
                    uint32_t ox = sm + C_OX + ln * 8;
                    uint8_t* a4 = acc + (ln >> 3) * 256 + (ln & 7) * 16; uint8_t* a1 = acc + 1024 + ln * 4;
                    PIN(ox); PINL(a4); PINL(a1);
                    mbar_wait(sm + CB_XF, (s + 1) & 1);
#pragma unroll
                    for (int f = 0; f < NW; f++) ldsm4t(a[f], frag(f));
                    float e[2][4];
                    uint32_t ob[12][2];
                    bar_sync(B_OWN, 128 + 32 * nu);
#pragma unroll
                    for (int k = 0; k < 4; k++) lds64(ob[k], ox + k * 256);
#pragma unroll
                    for (int k = 0; k < 4; k++) {
                        SFENCE();
                        if (k > 0) { ldsm4t(a[2 * k - 2 + NW], frag(2 * k - 2 + NW)); ldsm4t(a[2 * k - 1 + NW], frag(2 * k - 1 + NW)); }
                        if (k == 0) { mma16z(e[0], a[0], ob[0][0], ob[0][1]); mma16z(e[1], a[1], ob[0][0], ob[0][1]); }
                        else { mma16(e[0], a[2 * k], ob[k][0], ob[k][1]); mma16(e[1], a[2 * k + 1], ob[k][0], ob[k][1]); }
                    }
                    SFENCE();
                    ldsm4t(a[6 + NW], frag(6 + NW)); ldsm4t(a[7 + NW], frag(7 + NW));
                    PINL(xo); PINL(xt);
                    if (warp == 0) PROF(3);
                    mbar_wait(sm + CB_OX, s & 1);
#pragma unroll
                    for (int k = 4; k < 4 + OD; k++) lds64(ob[k], ox + k * 256);
                    if (warp == 1) PROF(4);
#pragma unroll
                    for (int k = 4; k < 12; k++) {
                        SFENCE();
                        if (k > 4 && k - 1 + OD < 12) lds64(ob[k - 1 + OD], ox + (k - 1 + OD) * 256);
                        if (k > 4 && 2 * k - 2 + NW < 24) { ldsm4t(a[2 * k - 2 + NW], frag(2 * k - 2 + NW)); ldsm4t(a[2 * k - 1 + NW], frag(2 * k - 1 + NW)); }
                        mma16(e[0], a[2 * k], ob[k][0], ob[k][1]); mma16(e[1], a[2 * k + 1], ob[k][0], ob[k][1]);
                    }
                    asm volatile("red.relaxed.gpu.global.add.noftz.v4.f16x2 [%0], {%1,%2,%3,%4};" :: "l"(a4), "r"(packh(e[0][0], e[0][1])), "r"(packh(e[0][2], e[0][3])),
                                 "r"(packh(e[1][0], e[1][1])), "r"(packh(e[1][2], 1.f)) : "memory");
                    asm volatile("red.relaxed.gpu.global.add.noftz.f16x2 [%0], %1;" :: "l"(a1), "r"(packh(e[1][3], 1.f)) : "memory");
                    bar_arrive(B_RED, 384);
                    if (warp == 0) { PROF(5); PROFG(25); }
                }
            }
            float acc[16];
#pragma unroll
            for (int i = 0; i < 16; i++) acc[i] = 0.f;
            if (warp == 1) PROF(12);
            WG_FENCE();
#pragma unroll
            for (int n = 0; n < 40; n++) {
                const int i = n < 24 ? n : n < 32 ? n + 4 : n < 36 ? n - 8 : n, ks = pair_idx(i >> 1) * 2 + (i & 1);
                if (n == 32) mbar_wait(sm + CB_XG, (s + 1) & 1);
                wgmma_rs_n32(acc, wa[i], (pair_own(i >> 1) ? xo : xt) + (((ks >> 2) * 4096 + (ks & 3) * 32) >> 4));
                if (n % 4 == 2 && n / 4 < NP) { SFENCE(); ldsm4t(pl[n / 4], wvrd + n / 4 * 2048); }
            }
            WG_COMMIT();
            WG_WAIT(0);
            if (warp == 1) PROF(13);
            bar_sync(B_X, 256);
            uint32_t lx = l16; PIN(lx);
            const uint32_t dst = (lx ^ (lx >> 3 & 48)) + C_QX + wg * 20480 + w * 1024;
            sts128(dst, pack2(acc[0], acc[1]), pack2(acc[4], acc[5]), pack2(acc[8], acc[9]), pack2(acc[12], acc[13]));
            sts128(dst + 512, pack2(acc[2], acc[3]), pack2(acc[6], acc[7]), pack2(acc[10], acc[11]), pack2(acc[14], acc[15]));
            if (warp == 1) PROF(14);
            s++;
        }
    } else {
        asm volatile("setmaxnreg.dec.sync.aligned.u32 56;");
        const uint32_t l16 = opaque(sm + lane * 16);
        bar_sync(B_OWN, 384);
        if (w == 0 && elect()) {
            mbar_expect(sm + CB_W2, 81920 + nu * 12288);
#pragma unroll 1
            for (int c = 0; c < 10; c++) tma2d(sm + C_WV + c * 8192, &mp.wv, col0, c * 64, sm + CB_W2);
        }
        if (w == 1 && elect()) {
#pragma unroll 1
            for (int c = 0; c < 3 * nu; c++) tma2d(sm + C_WO + c * 4096, &mp.wo, (u0 + c / 3) * 32, head * DH + (c + j) % 3 * 64, sm + CB_W2);
        }
        if (w == 2 && elect()) {
            flag_wait(&g_flags.v[head], 2);
            mbar_expect(sm + CB_VX, 4096);
            bulk_g2s(sm + C_VX, rec0 + j * 4096, 4096, sm + CB_VX);
        }
        __syncwarp();
        uint32_t mx;
        {
            mx = 0;
#pragma unroll 1
            for (int i = 0; i < 20; i++) {
                const int o = w * 20 + i, c = o * 8 + (lane >> 2), t = (lane & 3) * 2;
                const uint32_t v = (uint32_t)__ldg((const unsigned short*)ar.mem0 + t * DM + c) | (uint32_t)__ldg((const unsigned short*)ar.mem0 + (t + 1) * DM + c) << 16;
                sts32(sm + C_MEM + o * 128 + lane * 4, v); mx = absmax2(mx, v);
            }
            sts32(sm + C_SCL, 0x3f800000u);
        }
        int ex = 0;
        bool chk = false;
        int nslow = 0;
        uint32_t vb[2][4];
        { const uint32_t vxrd = l16 + lane * 112 + (((2 * w) ^ vswz(lane)) << 4); mbar_wait(sm + CB_VX, 0); ldsm4t(vb[0], vxrd + C_VX); ldsm4t(vb[1], (vxrd ^ 16) + C_VX); }
        bar_sync(B_MEM, 384);
        for (int s = 0; s < NSEG; s++) {
            uint32_t lq = l16; PIN(lq);
            const uint32_t l0 = lq >> 4 & 31, r0 = l0 & 7, m0 = l0 >> 3;
            uint32_t kb[2][4];
            const uint32_t kxrd = sm + C_KX + l0 * 64 + ((w ^ (r0 >> 1)) << 4);
            ldsm4t(kb[0], kxrd); ldsm4t(kb[1], kxrd + 2048);
            if (w == 0 && s + 1 < NSEG && elect()) {
                h_fetch_a(mp, sm, s + 1);
                mbar_expect(sm + CB_VX, 4096);
                bulk_g2s(sm + C_VX, rec0 + (size_t)(s + 1) * (NH * REC) + j * 4096, 4096, sm + CB_VX);
            }
            __syncwarp();
            const uint32_t r1 = j == 2 ? -(2 << 24) : 1 << 24, r2 = j == 0 ? 2 << 24 : -(1 << 24);
            uint32_t qrd = sm + C_QM + ((m0 >> 1) + 2 * (m0 & 1)) * 128 + r0 * 16, scdst = sm + C_SC + j * 640 + w * 128 + ((l0 * 4) ^ (w * 32)),
                     sc1 = scdst + r1, sc2 = scdst + r2;
            PIN(qrd); PIN(scdst); PIN(sc1); PIN(sc2);
            for (;;) {
                sts32(sm + C_MAX + w * 4, __reduce_max_sync(0xffffffffu, max(mx & 0xffffu, mx >> 16)) >> 7);
                bar_sync(B_AUX, 128);
                uint32_t m4[4]; lds128(m4, sm + C_MAX);
                const int m = __shfl_sync(0xffffffffu, max(max(m4[0], m4[1]), max(m4[2], m4[3])), 0);
                const bool bad = chk && (m == 255 || m < 127 - 6 || ar.force);
                ex = min(max(ex + 130 - m, -40), 40);
                sts32(sm + C_BAD, bad);
                if (!bad) break;
                bar_sync(B_QK, 384);
                bar_sync(B_RED, 384);
                nslow++;
                if (w == 0 && elect()) {
                    asm volatile("red.release.gpu.global.add.u32 [%0], 1;" :: "l"(&g_flags.slow) : "memory");
                    for (int n = 0;; n++) {
                        uint32_t v; asm volatile("ld.acquire.gpu.global.u32 %0, [%1];" : "=r"(v) : "l"(&g_flags.slow) : "memory");
                        if (v >= 96u * nslow) break;
                        if (n > (1 << 23)) __trap();
                    }
                }
                bar_sync(B_AUX, 128);
                mx = 0;
#pragma unroll 1
                for (int i = 0; i < 10; i++) {
                    float4 a = make_float4(0, 0, 0, 0);
#pragma unroll 4
                    for (int h = 0; h < NH; h++) {
                        const float4 v = __ldcg((const float4*)(g_slow + ((((s & 1) * NH + h) * 20 + w * 5 + (i >> 1)) * 32 + l0) * 8) + (i & 1));
                        a.x += v.x; a.y += v.y; a.z += v.z; a.w += v.w;
                    }
                    const uint32_t o0 = pack2(a.x, a.y), o1 = pack2(a.z, a.w);
                    sts32(sm + C_MEM + (w * 10 + i) * 256 + l0 * 4, o0); sts32(sm + C_MEM + (w * 10 + i) * 256 + 128 + l0 * 4, o1);
                    mx = absmax2(absmax2(mx, o0), o1);
                }
                sts32(sm + C_SCL, 0x3f800000u);
                ex = 0; chk = false;
                bar_sync(B_MEM, 384);
            }
            if (s + 1 == NSEG) {
                bar_sync(B_QK, 384);
                bar_sync(B_VP, 384);
                const float4 y0 = lds128f(lq + C_VP + w * 512), y1 = lds128f(lq + C_VP + w * 512 + 2048);
                sts32(sm + C_VM + w * 256 + l0 * 4, pack2(y0.x + y1.x, y0.y + y1.y)); sts32(sm + C_VM + w * 256 + 128 + l0 * 4, pack2(y0.z + y1.z, y0.w + y1.w));
                bar_arrive(B_VM, 160);
                break;
            }
            if (w == 3) {
                uint32_t qa[2][4], km[2][4], x, y;
                bar_sync(B_QK, 384);
                ldsm4t(qa[0], qrd); ldsm4t(km[0], lq + C_KM); ldsm4t(qa[1], qrd + 512); ldsm4t(km[1], lq + C_KM + 512);
                SFENCE();
                score_tiles(qa, kb, km, x, y);
                stas1(sc1, x, sm + CB_SC + r1); stas1(sc2, x, sm + CB_SC + r2); stas1(sc1 + 128, y, sm + CB_SC + r1); stas1(sc2 + 128, y, sm + CB_SC + r2);
                sts32(scdst, x); sts32(scdst + 128, y);
            } else {
                uint32_t qa[2][4];
                bar_sync(B_QK, 384);
                ldsm4t(qa[0], qrd); ldsm4t(qa[1], qrd + 512);
                if (w == 0) PROF(6);
                const uint32_t x = score_tile(qa, kb);
                stas1(sc1, x, sm + CB_SC + r1); stas1(sc2, x, sm + CB_SC + r2);
                sts32(scdst, x);
            }
            __syncwarp();
            if (elect()) mbar_arrive(sm + CB_SC);
            SFENCE();
            if (w == 0) PROF(7);
            uint32_t scrd = sm + C_SC + (l0 & 3) * 128 + (((l0 >> 2) ^ (2 * (l0 & 3))) << 4), zrd = sm + C_SC + 512 + ((l0 * 4) ^ 96),
                     od = sm + C_OX + l0 * 8 + w * 256, od1 = od + r1 + 2048, od2 = od + r2 + 1024, vprd = lq + C_VP + w * 512, vmst = sm + C_VM + w * 256 + l0 * 4, ones = 0x3f803f80u, ones2 = 0x3f803f80u, zero = 0;
            PIN(scrd); PIN(zrd); PIN(od); PIN(od1); PIN(od2); PIN(vprd); PIN(vmst); PIN(ones); PIN(ones2); PIN(zero);
            mbar_wait(sm + CB_SC, s & 1);
            float sv[10];
            {
                uint32_t x[3][4], z[3];
#pragma unroll
                for (int p = 0; p < 3; p++) { lds128(x[p], scrd + p * 640); z[p] = lds32(zrd + p * 640); }
                if (w == 1) PROF(8);
#pragma unroll
                for (int i = 0; i < 4; i++) { sv[2 * i] = (lo_f(x[0][i]) + lo_f(x[1][i])) + lo_f(x[2][i]); sv[2 * i + 1] = (hi_f(x[0][i]) + hi_f(x[1][i])) + hi_f(x[2][i]); }
                sv[8] = (lo_f(z[0]) + lo_f(z[1])) + lo_f(z[2]); sv[9] = (hi_f(z[0]) + hi_f(z[1])) + hi_f(z[2]);
            }
            float mxs = fmaxf(fmaxf(fmaxf(sv[0], sv[1]), fmaxf(sv[2], sv[3])), fmaxf(fmaxf(fmaxf(sv[4], sv[5]), fmaxf(sv[6], sv[7])), fmaxf(sv[8], sv[9])));
            {
                const float a = __shfl_xor_sync(0xffffffffu, mxs, 1), b = __shfl_xor_sync(0xffffffffu, mxs, 2), c = __shfl_xor_sync(0xffffffffu, mxs, 3);
                SFENCE();
                bar_sync(B_VP, 384);
                mxs = fmaxf(fmaxf(mxs, a), fmaxf(b, c));
            }
            const float4 y0 = lds128f(vprd), y1 = lds128f(vprd + 2048);
            const uint32_t pm = pack2(ex2(sv[8] - mxs), ex2(sv[9] - mxs));
            uint32_t pa[4];
            pa[0] = pack2(ex2(sv[0] - mxs), ex2(sv[1] - mxs)); pa[2] = pack2(ex2(sv[2] - mxs), ex2(sv[3] - mxs));
            const uint32_t vm0 = pack2(y0.x + y1.x, y0.y + y1.y), vm1 = pack2(y0.z + y1.z, y0.w + y1.w);
            float o[2][4], o2[2][4], sm_[4];
            mma8z(sm_, pm, zero, ones); mma8z(o[0], pm, zero, vm0); mma8z(o[1], pm, zero, vm1);
            sts32(vmst, vm0); sts32(vmst + 128, vm1);
            SFENCE();
            pa[1] = pack2(ex2(sv[4] - mxs), ex2(sv[5] - mxs)); pa[3] = pack2(ex2(sv[6] - mxs), ex2(sv[7] - mxs));
            if (w == 2) PROF(9);
            {
                mma16(sm_, pa, ones, ones2);
                mma16(o[0], pa, vb[0][0], vb[0][1]); mma16z(o2[0], pa, vb[0][2], vb[0][3]);
                mma16(o[1], pa, vb[1][0], vb[1][1]); mma16z(o2[1], pa, vb[1][2], vb[1][3]);
                float inv; asm("rcp.approx.ftz.f32 %0, %1;" : "=f"(inv) : "f"(sm_[0] + sm_[2]));
                const float sc = __int_as_float((127 + ex) << 23);
                const uint32_t a = pack2((o[0][0] + o2[0][2]) * sc * inv, (o[0][1] + o2[0][3]) * sc * inv), b = pack2((o[1][0] + o2[1][2]) * sc * inv, (o[1][1] + o2[1][3]) * sc * inv);
                stas2(od1, a, b, sm + CB_OX + r1); stas2(od2, a, b, sm + CB_OX + r2);
                asm volatile("st.shared.v2.b32 [%0], {%1,%2};" :: "r"(od), "r"(a), "r"(b) : "memory");
                bar_arrive(B_OWN, 128 + 32 * nu);
                bar_arrive(B_VM, 160);
                if (w == 0) PROF(10);
            }
            const uint8_t* acc = g_acc + ((s + 1) >> 1) * 32768 + ((s + 1) & 1) * 128 + w * 6400;
            const uint8_t* a4 = acc + (l0 >> 3) * 256 + (l0 & 7) * 16; const uint8_t* a1 = acc + 1024 + l0 * 4;
            PINL(a4); PINL(a1);
            if (w == 1 && elect()) { mbar_expect(sm + CB_SC, 1280); sts32(sm + C_SCL, (127 - ex) << 23); }
            __syncwarp();
            bar_sync(B_RED, 384);
            SFENCE();
            const uint32_t tw = clock();
            SFENCE();
            if (w == 1 && elect()) mbar_expect(sm + CB_OX, 2048);
            __syncwarp();
            { const uint32_t vxrd = lq + l0 * 112 + (((2 * w) ^ vswz(l0)) << 4); mbar_wait(sm + CB_VX, (s + 1) & 1); ldsm4t(vb[0], vxrd + C_VX); ldsm4t(vb[1], (vxrd ^ 16) + C_VX); }
            wait_until(tw + ar.D);
            if (w == 2) PROF(16);
            uint32_t v[5][4], z[5];
            int n = 0;
#pragma unroll
            for (int i = 0; i < 5; i++) {
                asm volatile("ld.relaxed.gpu.global.v4.u32 {%0,%1,%2,%3}, [%4];" : "=r"(v[i][0]), "=r"(v[i][1]), "=r"(v[i][2]), "=r"(v[i][3]) : "l"(a4 + i * 1280) : "memory");
                asm volatile("ld.relaxed.gpu.global.u32 %0, [%1];" : "=r"(z[i]) : "l"(a1 + i * 1280) : "memory");
            }
            while (__any_sync(0xffffffffu, min(min(min(v[0][3], z[0]), min(v[1][3], z[1])), min(min(min(v[2][3], z[2]), min(v[3][3], z[3])), min(v[4][3], z[4]))) < 0x50000000u)) {
#pragma unroll
                for (int i = 0; i < 5; i++) {
                    asm volatile("{ .reg .pred q; setp.lt.u32 q, %3, 0x50000000;\n@q ld.relaxed.gpu.global.v4.u32 {%0,%1,%2,%3}, [%4]; }" : "+r"(v[i][0]), "+r"(v[i][1]), "+r"(v[i][2]), "+r"(v[i][3]) : "l"(a4 + i * 1280) : "memory");
                    asm volatile("{ .reg .pred q; setp.lt.u32 q, %0, 0x50000000;\n@q ld.relaxed.gpu.global.u32 %0, [%1]; }" : "+r"(z[i]) : "l"(a1 + i * 1280) : "memory");
                }
                if (++n > SPIN_LIMIT) __trap();
            }
            if (w == 0) { PROF(11); PROFV(15, n); }
#pragma unroll
            for (int i = 0; i < 5; i++) {
                v[i][0] = h2b(v[i][0]); v[i][1] = h2b(v[i][1]); v[i][2] = h2b(v[i][2]); v[i][3] = h2b_lo(v[i][3], z[i]);
                stsm4(lq + C_MEM + w * 2560 + i * 512, v[i][0], v[i][1], v[i][2], v[i][3]);
            }
            bar_sync(B_MEM, 384);
            SFENCE();
            mx = 0;
#pragma unroll
            for (int i = 0; i < 5; i++) mx = absmax2(absmax2(absmax2(absmax2(mx, v[i][0]), v[i][1]), v[i][2]), v[i][3]);
            chk = true;
        }
    }
}

struct SideMaps { CUtensorMap h, wv, ost, o, wo, slab3, slab2, ln[4], wgate, wup, wdown; };
struct Sched { uint16_t end[64]; uint8_t kind[64], block[64], lsplit[16], slab[16], lnst[16]; };
constexpr int SD_SL = REC / 3, SD_NSL = 12, SD_EPI = SD_NSL * SD_SL, SD_VEC = SD_EPI + 2 * 24576, SD_BAR = SD_VEC + 6400, SD_SMEM = SD_BAR + 512;
static_assert(SD_SMEM <= 232448, "side shared memory");

template <int NPC, bool V>
__device__ __forceinline__ void tile_out(const float (&acc)[8 * NPC], uint32_t eb, uint32_t efull, uint32_t eempty, int& eph, int w, int lane) {
    const int r = lane & 7, mi = lane >> 3, row = w * 16 + (mi & 1) * 8 + r;
    const uint32_t rb = V ? eb + (row >> 5) * 12288 + (row & 31) * 128 : eb + row * 128, sw = V ? vswz(row & 31) : r;
    mbar_wait(eempty, eph); eph ^= 1;
#pragma unroll
    for (int p = 0; p < NPC; p++) {
        const int oc = 2 * p + (mi >> 1);
        stsm4(rb + (oc >> 3) * (V ? 4096 : 8192) + (((oc & 7) ^ sw) << 4), pack2(acc[8 * p], acc[8 * p + 1]), pack2(acc[8 * p + 2], acc[8 * p + 3]),
              pack2(acc[8 * p + 4], acc[8 * p + 5]), pack2(acc[8 * p + 6], acc[8 * p + 7]));
    }
    PROXY_FENCE();
    __syncwarp();
    if (lane == 0) mbar_arrive(efull);
}

__device__ __forceinline__ void attn_tile(uint32_t base, uint32_t dst, uint32_t eempty, int eph, int mt, int lane) {
    const int r = lane & 7, mi = lane >> 3, g = lane >> 2, t = lane & 3;
    float sc[5][4];
#pragma unroll
    for (int n = 0; n < 5; n++) sc[n][0] = sc[n][1] = sc[n][2] = sc[n][3] = 0.f;
    const uint32_t qrd = base + R_Q + ((mi >> 1) * 8 + r) * 64 + (((2 * mt + (mi & 1)) ^ (r >> 1)) << 4), krd = base + R_K + lane * 64 + ((r >> 1) << 4);
#pragma unroll 2
    for (int k2 = 0; k2 < 6; k2++) {
        const uint32_t cb = (k2 >> 1) * R_J + (k2 & 1) * 2048;
        uint32_t a0[4], a1[4], bb[5][4];
        ldsm4t(a0, qrd + cb); ldsm4t(a1, qrd + cb + 1024);
#pragma unroll
        for (int n = 0; n < 4; n++) ldsm4t(bb[n], (krd ^ (n << 4)) + cb);
        ldsm4t(bb[4], base + R_KM + (k2 >> 1) * R_J + (k2 & 1) * 512 + lane * 16);
#pragma unroll
        for (int n = 0; n < 5; n++) mma16(sc[n], a0, bb[n][0], bb[n][1]);
#pragma unroll
        for (int n = 0; n < 5; n++) mma16(sc[n], a1, bb[n][2], bb[n][3]);
    }
    const float scale = 0.07216878364870322f, l2e = 1.4426950408889634f;
    float v[2][10], mx[2], sum[2];
#pragma unroll
    for (int hf = 0; hf < 2; hf++) {
        mx[hf] = -INFINITY;
#pragma unroll
        for (int n = 0; n < 5; n++) {
            uint32_t u = pack2(sc[n][2 * hf], sc[n][2 * hf + 1]);
            u = pack2(lo_f(u) * scale, hi_f(u) * scale);
            const int lim = 8 * (g >> 1) + 2 * (2 * mt + hf) + (g & 1) - 8 * t - 2 * n;
            v[hf][2 * n] = (n < 4 && lim < 0) ? -1e9f : lo_f(u);
            v[hf][2 * n + 1] = (n < 4 && lim < 1) ? -1e9f : hi_f(u);
            mx[hf] = fmaxf(mx[hf], fmaxf(v[hf][2 * n], v[hf][2 * n + 1]));
        }
    }
#pragma unroll
    for (int o = 1; o < 4; o <<= 1)
#pragma unroll
        for (int hf = 0; hf < 2; hf++) mx[hf] = fmaxf(mx[hf], __shfl_xor_sync(0xffffffffu, mx[hf], o));
#pragma unroll
    for (int hf = 0; hf < 2; hf++) {
        sum[hf] = 0;
#pragma unroll
        for (int q = 0; q < 10; q++) { asm("ex2.approx.ftz.f32 %0, %1;" : "=f"(v[hf][q]) : "f"((v[hf][q] - mx[hf]) * l2e)); sum[hf] += v[hf][q]; }
    }
#pragma unroll
    for (int o = 1; o < 4; o <<= 1)
#pragma unroll
        for (int hf = 0; hf < 2; hf++) sum[hf] += __shfl_xor_sync(0xffffffffu, sum[hf], o);
    uint32_t pa[5][2];
#pragma unroll
    for (int hf = 0; hf < 2; hf++) {
        const float inv = __fdividef(1.f, sum[hf]);
#pragma unroll
        for (int n = 0; n < 5; n++) pa[n][hf] = pack2(v[hf][2 * n] * inv, v[hf][2 * n + 1] * inv);
    }
    mbar_wait(eempty, eph);
    const uint32_t tok = 8 * (r >> 1) + 2 * mi + (r & 1), vrd = base + tok * 128 + (vswz(tok) << 4);
#pragma unroll 2
    for (int n4 = 0; n4 < 6; n4++) {
        const uint32_t c0 = (n4 & 1) * 4;
        uint32_t bm[4], bb[4][4];
        ldsm4(bm, base + R_VM + (n4 >> 1) * R_J + (n4 & 1) * 512 + lane * 16);
#pragma unroll
        for (int u = 0; u < 4; u++) ldsm4t(bb[u], (vrd ^ ((c0 + u) << 4)) + (n4 >> 1) * 4096);
        float o[4][4];
#pragma unroll
        for (int u = 0; u < 4; u++) mma8z(o[u], pa[4][0], pa[4][1], bm[u]);
#pragma unroll
        for (int u = 0; u < 4; u++) mma16(o[u], pa[0][0], pa[0][1], pa[1][0], pa[1][1], bb[u][0], bb[u][1]);
#pragma unroll
        for (int u = 0; u < 4; u++) mma16(o[u], pa[2][0], pa[2][1], pa[3][0], pa[3][1], bb[u][2], bb[u][3]);
#pragma unroll
        for (int p = 0; p < 2; p++)
            stsm4(dst + (n4 >> 1) * 8192 + ((mi & 1) * 8 + r) * 128 + (((c0 + 2 * p + (mi >> 1)) ^ r) << 4), pack2(o[2 * p][0], o[2 * p][1]), pack2(o[2 * p][2], o[2 * p][3]),
                  pack2(o[2 * p + 1][0], o[2 * p + 1][1]), pack2(o[2 * p + 1][2], o[2 * p + 1][3]));
    }
}

#define SPROF(tk, i)
#define FWAIT(bar, par) mbar_wait(bar, par)
#define EPROF()
#define TPROF(i)
__device__ __forceinline__ void side_tail(uint32_t wgu, uint32_t wgu_bar, int wgu_ph, uint32_t wd, uint32_t wd_bar, int wd_ph, uint32_t xb, uint32_t gbar, bf16* out, int tid) {
    const int warp = __shfl_sync(0xffffffffu, tid >> 5, 0), lane = tid & 31, r = lane & 7, mi = lane >> 3, blk = blockIdx.x;
    const uint32_t T_GU = xb, T_X = xb + 24576, T_RED = T_X + 10240, T_KEY = T_RED + 8192;
    TPROF(0);
    auto rkey = [](int idx) { uint32_t u = __ldcg((const unsigned short*)g_r + idx); u = (u & 0x8000u) ? (~u & 0xffffu) : (u | 0x8000u); return (u << 16) | (uint32_t)(S_TOK - 1 - idx); };
    {
        if (warp == 0 && lane < 15) flag_wait(&g_flags.ln[lane * 32], 128);
        bar_sync(1, 256);
        uint32_t k[8];
#pragma unroll
        for (int i = 0; i < 8; i++) { const int idx = warp * 240 + i * 32 + lane; k[i] = i * 32 + lane < 240 ? rkey(idx) : 0u; }
#pragma unroll 1
        for (int it = 0; it < 8; it++) {
            const uint32_t m = __reduce_max_sync(0xffffffffu, max(umax3(k[0], k[1], k[2]), max(umax3(k[3], k[4], k[5]), max(k[6], k[7]))));
#pragma unroll
            for (int i = 0; i < 8; i++) if (k[i] == m) k[i] = 0;
            if (lane == 0) sts32(T_KEY + (warp * 8 + it) * 4, m);
        }
    }
    bar_sync(1, 256);
    if (warp == 0) {
        uint32_t k[6];
        k[0] = lds32(T_KEY + lane * 4); k[1] = lds32(T_KEY + 128 + lane * 4);
        if (lane == 0) flag_wait(&g_flags.ln[15 * 32], 128);
        __syncwarp();
        TPROF(1);
#pragma unroll
        for (int i = 0; i < 4; i++) k[2 + i] = rkey(1920 + i * 32 + lane);
#pragma unroll 1
        for (int it = 0; it < 8; it++) {
            const uint32_t m = __reduce_max_sync(0xffffffffu, max(umax3(k[0], k[1], k[2]), umax3(k[3], k[4], k[5])));
#pragma unroll
            for (int i = 0; i < 6; i++) if (k[i] == m) k[i] = 0;
            if (lane == 0) sts32(T_KEY + 256 + it * 4, S_TOK - 1 - (m & 0xffffu));
        }
    }
    bar_sync(1, 256);
    TPROF(2);
    {
        const bf16* src = g_h2 + lds32(T_KEY + 256 + (tid & 7) * 4) * DM + (tid >> 3) * 8;
        uint4 v[3];
#pragma unroll
        for (int i = 0; i < 3; i++) if (i < 2 || tid < 128) v[i] = __ldcg((const uint4*)(src + i * 256));
#pragma unroll
        for (int i = 0; i < 3; i++) if (i < 2 || tid < 128) sts128(T_X + tid * 16 + i * 4096, v[i].x, v[i].y, v[i].z, v[i].w);
    }
    const int trow = lds32(T_KEY + 256 + (lane >> 2) * 4), tcol = (blk < 80 ? blk : 0) * 8 + (lane & 3) * 2;
    const uint32_t fx1 = __ldcg((const uint32_t*)(g_x1 + trow * DM + tcol)), fh2 = __ldcg((const uint32_t*)(g_h2 + trow * DM + tcol)),
                   fgb = __ldcg((const uint32_t*)(g_mod + 5 * DM + tcol));
    const float fr = __uint_as_float((uint32_t)__ldcg((const unsigned short*)g_r + trow) << 16);
    mbar_wait(wgu_bar, wgu_ph);
    bar_sync(1, 256);
    TPROF(3);
    {
        float dg[4] = {0, 0, 0, 0}, du[4] = {0, 0, 0, 0};
#pragma unroll
        for (int k = 0; k < 5; k++) {
            uint32_t b[4], ag[4], au[4];
            ldsm4(b, T_X + (warp * 5 + k) * 256 + (lane & 15) * 16);
            const uint32_t o = ((warp * 5 + k) * 16 + (mi >> 1) * 8 + r) * 32 + (mi & 1) * 16;
            ldsm4t(ag, wgu + o); ldsm4t(au, wgu + 20480 + o);
            mma16(dg, ag, b[0], b[1]); mma16(du, au, b[0], b[1]);
        }
        sts128f(T_RED + warp * 1024 + lane * 16, dg[0], dg[1], dg[2], dg[3]); sts128f(T_RED + warp * 1024 + 512 + lane * 16, du[0], du[1], du[2], du[3]);
    }
    bar_sync(1, 256);
    if (warp == 0) {
        float g4[4] = {0, 0, 0, 0}, u4[4] = {0, 0, 0, 0};
#pragma unroll
        for (int i = 0; i < 8; i++) {
            const float4 a = lds128f(T_RED + i * 1024 + lane * 16), b = lds128f(T_RED + i * 1024 + 512 + lane * 16);
            g4[0] += a.x; g4[1] += a.y; g4[2] += a.z; g4[3] += a.w; u4[0] += b.x; u4[1] += b.y; u4[2] += b.z; u4[3] += b.w;
        }
        float y[4];
#pragma unroll
        for (int i = 0; i < 4; i++) { const float gq = bfr(g4[i]); y[i] = bfr(__fdividef(gq, 1.f + __expf(-gq))) * bfr(u4[i]); }
        g_gu[blk * 64 + lane] = movm_t(pack2(y[0], y[1])); g_gu[blk * 64 + 32 + lane] = movm_t(pack2(y[2], y[3]));
        __syncwarp();
        TPROF(4);
        if (lane == 0) {
            flag_add(&g_flags.gu);
            if (blk < 80) {
                flag_wait(&g_flags.gu, 96);
                mbar_expect(gbar, 24576); bulk_g2s(T_GU, g_gu, 24576, gbar);
            }
        }
        __syncwarp();
    }
    if (blk < 80) {
        mbar_wait(wd_bar, wd_ph);
        mbar_wait(gbar, 0);
        TPROF(5);
        float d[2][4] = {{0, 0, 0, 0}, {0, 0, 0, 0}};
#pragma unroll
        for (int k2 = 0; k2 < 6; k2++) {
            uint32_t b[4]; ldsm4t(b, wd + (warp * 6 + k2) * 512 + lane * 16);
#pragma unroll
            for (int h = 0; h < 2; h++) {
                uint32_t a[4]; ldsm4(a, T_GU + ((warp * 12 + k2 * 2 + h) * 2 + (mi >> 1)) * 128 + r * 16);
                mma16(d[h], a, b[2 * h], b[2 * h + 1]);
            }
        }
        asm volatile("st.shared.v2.f32 [%0], {%1,%2};" :: "r"(T_X + warp * 256 + lane * 8), "f"(d[0][0] + d[1][0]), "f"(d[0][1] + d[1][1]) : "memory");
        bar_sync(1, 256);
        if (warp == 0) {
            float y0 = 0, y1 = 0;
#pragma unroll
            for (int i = 0; i < 8; i++) { const float2 a = lds64f(T_X + i * 256 + lane * 8); y0 += a.x; y1 += a.y; }
            const float sg = bfr(__fdividef(1.f, 1.f + __expf(-fr)));
            const float b0 = bfr(lo_f(fh2) + bfr(bfr(y0) * sg)), b1 = bfr(hi_f(fh2) + bfr(bfr(y1) * sg));
            *(uint32_t*)(out + trow * DM + tcol) = pack2(lo_f(fx1) + bfr(lo_f(fgb) * b0), hi_f(fx1) + bfr(hi_f(fgb) * b1));
        }
    }
    TPROF(6);
}

__global__ void __launch_bounds__(384, 1) k_side(const __grid_constant__ SideMaps mp, const __grid_constant__ Sched sd, const bf16* __restrict__ x,
                                                 const bf16* __restrict__ wr, bf16* __restrict__ out) {
    extern __shared__ __align__(1024) uint8_t smraw[];
    const uint32_t sm = smem_u32(smraw);
    if (sm & 1023) __trap();
    const uint32_t FULL = sm + SD_BAR, EMPTY = FULL + 96, EFULL = FULL + 192, EEMPTY = EFULL + 16, IFULL = EFULL + 32, IEMPTY = EFULL + 64, IQ = EFULL + 96,
                   VEC = EFULL + 112, GBAR = EFULL + 120, LNDONE = EFULL + 128, LNFREE = EFULL + 136;
    const int tid = threadIdx.x, warp = __shfl_sync(0xffffffffu, tid >> 5, 0), lane = tid & 31;
    const uint64_t ef = policy_stream();
    if (tid >= 32 && tid < 32 + SD_NSL) { mbar_init(FULL + 8 * (tid - 32), 1); mbar_init(EMPTY + 8 * (tid - 32), 8); asm volatile("fence.mbarrier_init.release.cluster;" ::: "memory"); }
    if (tid == 0) {
        for (int i = 0; i < 2; i++) { mbar_init(EFULL + 8 * i, 4); mbar_init(EEMPTY + 8 * i, 1); }
        for (int i = 0; i < 4; i++) { mbar_init(IFULL + 8 * i, 1); mbar_init(IEMPTY + 8 * i, 11); }
        mbar_init(VEC, 1); mbar_init(GBAR, 1); mbar_init(LNDONE, 8); mbar_init(LNFREE, 1);
        asm volatile("fence.mbarrier_init.release.cluster;" ::: "memory");
    }
    __syncthreads();
    if (warp >= 8) {
      asm volatile("setmaxnreg.dec.sync.aligned.u32 40;");
      if (warp == 8) {
        auto claim = []() { uint32_t v; asm volatile("{ .reg .pred e; elect.sync _|e, -1; mov.u32 %0, 0; @e atom.relaxed.gpu.global.add.u32 %0, [%1], 1; }" : "=r"(v) : "l"(&g_flags.next) : "memory"); return v; };
        flag_wait_warp(&g_flags.h, 160);
        uint32_t nxt = claim();
        if (elect()) {
            flags_release();
            mbar_expect(VEC, 6400); bulk_g2s(sm + SD_VEC, g_mod + 2 * DM, 5120, VEC); bulk_g2s(sm + SD_VEC + 5120, wr, 1280, VEC);
        }
        __syncwarp();
        int st = 0, ph = 1, run = 0;
        auto take = [&](int n, int bytes) {
            mbar_wait(EMPTY + 8 * (st + n - 1), ph);
            asm volatile("{ .reg .pred p; setp.lt.u32 p, %2, %3; @p mbarrier.arrive.expect_tx.shared::cta.b64 _, [%0], %1; }"
                :: "r"(FULL + 8 * (st + lane)), "r"(lane ? 0 : bytes), "r"(lane), "r"(n) : "memory");
        };
        auto step = [&](int n) { st += n; if (st == SD_NSL) { st = 0; ph ^= 1; } };
#pragma unroll 1
        for (int q = 0;; q++) {
            const int tk = __reduce_max_sync(0xffffffffu, nxt);
            while (run < 64 && tk >= sd.end[run]) run++;
            const int kind = run < 64 ? sd.kind[run] : 4, b = sd.block[run & 63], i = tk - (run ? sd.end[run - 1] : 0), ls = sd.lsplit[b];
            mbar_wait(IEMPTY + 8 * (q & 3), ((q >> 2) & 1) ^ 1);
            if (elect()) {
                sts32(IQ + 4 * (q & 3), kind << 12 | b << 8 | (i & 255));
                mbar_arrive(IFULL + 8 * (q & 3));
            }
            __syncwarp();
            const int pad = kind == 2 ? st & 1 : (12 - st) % 3;
            if (pad) { take(pad, 0); step(pad); }
            if (kind == 0) {
#pragma unroll 1
                for (int kb = 0; kb < 10; kb++) {
                    take(3, 40960);
                    if (elect()) { tma2d(sm + st * SD_SL, &mp.h, kb * 64, b * 128, FULL + 8 * st); tma3d(sm + st * SD_SL + 16384, &mp.wv, kb * 64, i * 3, FULL + 8 * st); }
                    if (kb == 8) nxt = claim();
                    step(3);
                }
            } else if (kind == 1) {
                if (elect())
                    asm volatile("cp.async.bulk.prefetch.L2.global [%0], 5120;" :: "l"(x + (b * 128 + i * 4) * DM) : "memory");
                const bool all = __all_sync(0xffffffffu, ld_rlx(&g_flags.seg[(b * 4 + (lane & 3)) * 32 + i]) >= 3);
#pragma unroll 1
                for (int kb = 0; kb < 4; kb++) {
                    take(3, REC);
                    if (!all) flag_wait_warp(&g_flags.seg[(b * 4 + kb) * 32 + i], 3);
                    if (elect()) bulk_g2s_ef(sm + st * SD_SL, g_rec + (size_t)((b * 4 + kb) * NH + i) * REC, REC, FULL + 8 * st, ef);
                    if (kb == 2) nxt = claim();
                    step(3);
                }
            } else if (kind == 2) {
                const int nst = 192 >> ls;
#pragma unroll 1
                for (int kb = 0; kb < nst; kb++) {
                    const int k0 = ((i >> 1) * nst + kb) * 32;
                    take(2, 28672);
                    if (kb == 0) {
                        if (elect()) tma3d(sm + st * SD_SL + 8192, &mp.wo, k0, (i & 1) * 5, FULL + 8 * st);
                        flag_wait_warp(&g_flags.at[b * 32 + (i >> 1) * (32 >> ls) + (lane & ((32 >> ls) - 1))], 2);
                        if (elect()) tma2d(sm + st * SD_SL, &mp.o, k0, b * 128, FULL + 8 * st);
                    } else if (elect()) { tma3d(sm + st * SD_SL + 8192, &mp.wo, k0, (i & 1) * 5, FULL + 8 * st); tma2d(sm + st * SD_SL, &mp.o, k0, b * 128, FULL + 8 * st); }
                    if (kb == nst - 2) nxt = claim();
                    step(2);
                }
            } else if (kind == 3) {
                const int nst = sd.lnst[b];
                flag_wait_warp(&g_flags.o[b * 32], 4u << ls);
#pragma unroll 1
                for (int kb = 0; kb < nst; kb++) {
                    take(3, 40960);
                    if (elect())
                        asm volatile("cp.async.bulk.tensor.4d.shared::cluster.global.mbarrier::complete_tx::bytes.L2::cache_hint [%0], [%1, {0, 0, %3, %4}], [%2], %5;"
                            :: "r"(sm + st * SD_SL), "l"((uint64_t)&mp.ln[ls - 2]), "r"(FULL + 8 * st), "r"((i * nst + kb) * (32 >> ls)), "r"((int)sd.slab[b]), "l"(ef) : "memory");
                    step(3);
                }
                nxt = claim();
            } else {
                if (blockIdx.x < 96) {
                    take(3, 40960);
                    if (elect()) {
#pragma unroll 1
                        for (int c = 0; c < 5; c++) { tma2d(sm + st * SD_SL + c * 4096, &mp.wgate, blockIdx.x * 16, c * 128, FULL + 8 * st); tma2d(sm + st * SD_SL + 20480 + c * 4096, &mp.wup, blockIdx.x * 16, c * 128, FULL + 8 * st); }
                    }
                    step(3);
                }
                if (blockIdx.x < 80) {
                    take(3, 24576);
                    if (elect()) {
#pragma unroll 1
                        for (int c = 0; c < 6; c++) tma2d(sm + st * SD_SL + c * 4096, &mp.wdown, blockIdx.x * 8, c * 256, FULL + 8 * st);
                    }
                }
                break;
            }
        }
      } else {
        if (lane == 0) {
            const int wg = warp - 9; int ph = 0;
            for (int q = 0;; q++) {
                mbar_wait(IFULL + 8 * (q & 3), (q >> 2) & 1);
                const int it = lds32(IQ + 4 * (q & 3));
                mbar_arrive(IEMPTY + 8 * (q & 3));
                const int kind = (it >> 12) & 7, b = (it >> 8) & 15, i = it & 255;
                if (kind == 4) break;
                if (wg == 2) {
                    if (kind == 3) {
                        mbar_wait(LNDONE, ph); ph ^= 1;
                        mbar_arrive(LNFREE);
                        flag_add(&g_flags.ln[b * 32], sd.lnst[b] << (5 - sd.lsplit[b]));
                    }
                    continue;
                }
                if (kind == 3) continue;
                for (int rd = 0; rd < (kind == 2 ? 2 : 1); rd++) {
                    mbar_wait(EFULL + 8 * wg, ph); ph ^= 1;
                    const uint32_t src = sm + SD_EPI + wg * 24576;
                    if (kind == 2) tma3d_store(rd ? &mp.slab2 : &mp.slab3, (sd.slab[b] + (i >> 1)) * 128 + wg * 64, (i & 1) * 5 + rd * 3, src, ef, EF & 4);
                    else if (kind == 1) tma3d_store(&mp.ost, b * 128 + wg * 64, i * 3, src, ef, EF & 8);
                    else {
                        uint8_t* dst = g_rec + (size_t)((b * 4 + wg * 2) * NH + i) * REC;
                        if (EF & 2) { bulk_s2g_ef(dst, src, 12288, ef); bulk_s2g_ef(dst + NH * REC, src + 12288, 12288, ef); }
                        else { bulk_s2g(dst, src, 12288); bulk_s2g(dst + NH * REC, src + 12288, 12288); }
                    }
                    BULK_COMMIT();
                    BULK_WAIT_READ();
                    mbar_arrive(EEMPTY + 8 * wg);
                }
                BULK_WAIT();
                bump(kind == 0 ? &g_flags.v[b * 32 + i] : kind == 1 ? &g_flags.at[b * 32 + i] : &g_flags.o[b * 32]);
            }
        }
      }
    } else {
        asm volatile("setmaxnreg.inc.sync.aligned.u32 232;");
        const int wg = warp >> 2, w = warp & 3;
        int st = 0, ph = 0, eph = 1, lph = 1;
        const uint32_t eb = sm + SD_EPI + wg * 24576;
        for (int q = 0;; q++) {
            mbar_wait(IFULL + 8 * (q & 3), (q >> 2) & 1);
            const int itc = __shfl_sync(0xffffffffu, lds32(IQ + 4 * (q & 3)), 0);
            if (lane == 0) mbar_arrive(IEMPTY + 8 * (q & 3));
            const int kind = (itc >> 12) & 7, b = (itc >> 8) & 15, i = itc & 255;
            const int ns = kind == 2 ? 2 : 3, pad = kind == 2 ? st & 1 : (12 - st) % 3;
            if (pad) {
                mbar_wait(FULL + 8 * st, ph);
                if (lane < pad) mbar_arrive(EMPTY + 8 * (st + lane));
                st += pad; if (st == SD_NSL) { st = 0; ph ^= 1; }
            }
            const uint32_t rel = EMPTY + 8 * lane;
            if (kind == 0) {
                float acc[96];
#pragma unroll
                for (int n = 0; n < 96; n++) acc[n] = 0.f;
                int prev = -1;
                for (int kb = 0; kb < 10; kb++) {
                    FWAIT(FULL + 8 * st, ph);
                    const uint32_t base = sm + st * SD_SL;
                    WG_FENCE();
#pragma unroll
                    for (int ks = 0; ks < 4; ks++)
                        wgmma_ss_n192_tb(acc, mkdesc(base + wg * 8192 + ks * 32, 16, 1024), mkdesc(base + 16384 + ks * 2048, 8192, 1024), (kb | ks) != 0);
                    WG_COMMIT();
                    if (prev >= 0) { WG_WAIT(1); if (lane < ns) mbar_arrive(rel + 8 * prev); }
                    prev = st;
                    st += ns; if (st == SD_NSL) { st = 0; ph ^= 1; }
                }
                WG_WAIT(0);
                if (lane < ns) mbar_arrive(rel + 8 * prev);
                EPROF();
                tile_out<12, true>(acc, eb, EFULL + 8 * wg, EEMPTY + 8 * wg, eph, w, lane);
            } else if (kind == 1) {
                for (int kb = 0; kb < 4; kb++) {
                    FWAIT(FULL + 8 * st, ph);
                    if (kb == warp >> 1) {
                        attn_tile(sm + st * SD_SL, eb + (w * 16) * 128, EEMPTY + 8 * wg, eph, warp & 1, lane);
                        eph ^= 1;
                        PROXY_FENCE();
                        __syncwarp();
                        if (lane == 0) mbar_arrive(EFULL + 8 * wg);
                    }
                    if (lane < 3) mbar_arrive(rel + 8 * st);
                    st += ns; if (st == SD_NSL) { st = 0; ph ^= 1; }
                }
            } else if (kind == 2) {
                float acc[96], acc2[64];
#pragma unroll
                for (int n = 0; n < 96; n++) acc[n] = 0.f;
#pragma unroll
                for (int n = 0; n < 64; n++) acc2[n] = 0.f;
                int prev = -1;
                for (int kb = 192 >> sd.lsplit[b]; kb > 0; kb--) {
                    const uint32_t base = sm + st * SD_SL;
                    FWAIT(FULL + 8 * st, ph);
                    WG_FENCE();
#pragma unroll
                    for (int ks = 0; ks < 2; ks++) {
                        const uint64_t da = (mkdesc(base + wg * 4096 + ks * 32, 16, 512) & ~(3ull << 62)) | (2ull << 62);
                        wgmma_ss_n192_tb(acc, da, mkdesc(base + 8192 + ks * 2048, 4096, 1024), 1);
                        wgmma_ss_n128_tb(acc2, da, mkdesc(base + 8192 + 3 * 4096 + ks * 2048, 4096, 1024), 1);
                    }
                    WG_COMMIT();
                    if (prev >= 0) { WG_WAIT(1); if (lane < ns) mbar_arrive(rel + 8 * prev); }
                    prev = st;
                    st += ns; if (st == SD_NSL) { st = 0; ph ^= 1; }
                }
                WG_WAIT(0);
                if (lane < ns) mbar_arrive(rel + 8 * prev);
                EPROF();
                tile_out<12, false>(acc, eb, EFULL + 8 * wg, EEMPTY + 8 * wg, eph, w, lane);
                tile_out<8, false>(acc2, eb, EFULL + 8 * wg, EEMPTY + 8 * wg, eph, w, lane);
            } else if (kind == 3) {
                const int ls = sd.lsplit[b], nst = sd.lnst[b], rs = 5 - ls;
                const int lr = warp & ((1 << rs) - 1), per = 8 >> rs;
                auto row_of = [&](int kb) { const int pos = ((i * nst + kb) << rs) + lr; return b * 128 + (pos & 96) + 8 * ((pos & 7) >> 1) + 2 * ((pos >> 3) & 3) + (pos & 1); };
                uint2 xn[5];
                if ((warp >> rs) < nst) {
#pragma unroll
                    for (int q2 = 0; q2 < 5; q2++) xn[q2] = ld_ef(x + row_of(warp >> rs) * DM + lane * 4 + q2 * 128, ef);
                }
                mbar_wait(VEC, 0);
                for (int kb = 0; kb < nst; kb++) {
                    const int sst = st, sph = ph;
                    st += 3; if (st == SD_NSL) { st = 0; ph ^= 1; }
                    FWAIT(FULL + 8 * sst, sph);
                    if ((warp >> rs) != (kb & (per - 1))) {
                        if (lane < 3) mbar_arrive(rel + 8 * sst);
                        continue;
                    }
                    const int row = row_of(kb);
                    float av[20];
#pragma unroll
                    for (int n = 0; n < 20; n++) av[n] = 0.f;
                    uint32_t src = sm + sst * SD_SL + lr * 1280 + lane * 8;
#pragma unroll 1
                    for (int k = 0; k < (1 << ls); k += 4) {
                        uint32_t z[4][5][2];
#pragma unroll
                        for (int u = 0; u < 4; u++) {
#pragma unroll
                            for (int q2 = 0; q2 < 5; q2++) lds64(z[u][q2], src + q2 * 256);
                            src += 1280 << rs;
                        }
#pragma unroll
                        for (int u = 0; u < 4; u++)
#pragma unroll
                            for (int q2 = 0; q2 < 5; q2++) { av[4 * q2] += lo_f(z[u][q2][0]); av[4 * q2 + 1] += hi_f(z[u][q2][0]); av[4 * q2 + 2] += lo_f(z[u][q2][1]); av[4 * q2 + 3] += hi_f(z[u][q2][1]); }
                    }
                    __syncwarp();
                    if (lane < 3) mbar_arrive(rel + 8 * sst);
                    const uint32_t vec = sm + SD_VEC + lane * 8;
                    uint32_t xv[10], hv[10];
#pragma unroll
                    for (int q2 = 0; q2 < 5; q2++) {
                        uint32_t ga[2]; lds64(ga, vec + q2 * 256);
                        xv[2 * q2] = badd(xn[q2].x, bmul(ga[0], pack2(av[4 * q2], av[4 * q2 + 1])));
                        xv[2 * q2 + 1] = badd(xn[q2].y, bmul(ga[1], pack2(av[4 * q2 + 2], av[4 * q2 + 3])));
                    }
                    if (kb + per < nst) {
#pragma unroll
                        for (int q2 = 0; q2 < 5; q2++) xn[q2] = ld_ef(x + row_of(kb + per) * DM + lane * 4 + q2 * 128, ef);
                    }
                    ln_row(xv, hv);
                    float r0 = 0, r1 = 0;
#pragma unroll
                    for (int q2 = 0; q2 < 5; q2++) {
                        const int c = row * DM + lane * 4 + q2 * 128;
                        uint32_t sh[2], sc[2], gb[2], wv[2];
                        lds64(sh, vec + 1280 + q2 * 256); lds64(sc, vec + 2560 + q2 * 256); lds64(gb, vec + 3840 + q2 * 256); lds64(wv, vec + 5120 + q2 * 256);
                        const uint32_t h0 = badd(bmul(hv[2 * q2], badd(sc[0], 0x3f803f80u)), sh[0]), h1 = badd(bmul(hv[2 * q2 + 1], badd(sc[1], 0x3f803f80u)), sh[1]);
                        r0 += lo_f(h0) * lo_f(wv[0]) + hi_f(h0) * hi_f(wv[0]); r1 += lo_f(h1) * lo_f(wv[1]) + hi_f(h1) * hi_f(wv[1]);
                        st_ef(g_h2 + c, make_uint2(h0, h1), ef);
                        st_ef(g_x1 + c, make_uint2(xv[2 * q2], xv[2 * q2 + 1]), ef);
                        st_ef(out + c, make_uint2(badd(xv[2 * q2], bmul(gb[0], h0)), badd(xv[2 * q2 + 1], bmul(gb[1], h1))), ef);
                    }
                    const float rsum = warp_sum(r0 + r1);
                    if (lane == 0) g_r[row] = __float2bfloat16_rn(rsum);
                }
                __syncwarp();
                mbar_wait(LNFREE, lph); lph ^= 1;
                if (lane == 0) mbar_arrive(LNDONE);
            } else {
                if (blockIdx.x < 96) {
                    mbar_wait(EEMPTY + 8 * wg, eph);
                    int s1 = st + 3, p1 = ph; if (s1 == SD_NSL) { s1 = 0; p1 ^= 1; }
                    side_tail(sm + st * SD_SL, FULL + 8 * st, ph, sm + s1 * SD_SL, FULL + 8 * s1, p1, sm + SD_EPI, GBAR, out, tid);
                }
                break;
            }
        }
    }
    __syncwarp();
    asm volatile("griddepcontrol.wait;" ::: "memory");
}

typedef CUresult (*EncodeFn)(CUtensorMap*, CUtensorMapDataType, cuuint32_t, void*, const cuuint64_t*, const cuuint64_t*, const cuuint32_t*, const cuuint32_t*,
                             CUtensorMapInterleave, CUtensorMapSwizzle, CUtensorMapL2promotion, CUtensorMapFloatOOBfill);
static EncodeFn s_encode = nullptr;
static void make_map(CUtensorMap* m, const void* p, int rows, int cols, int box_rows, int box_cols = 64) {
    cuuint64_t dims[2] = {(cuuint64_t)cols, (cuuint64_t)rows}, strides[1] = {(cuuint64_t)cols * 2};
    cuuint32_t box[2] = {(cuuint32_t)box_cols, (cuuint32_t)box_rows}, es[2] = {1, 1};
    s_encode(m, CU_TENSOR_MAP_DATA_TYPE_BFLOAT16, 2, (void*)p, dims, strides, box, es, CU_TENSOR_MAP_INTERLEAVE_NONE,
             box_cols == 64 ? CU_TENSOR_MAP_SWIZZLE_128B : box_cols == 32 ? CU_TENSOR_MAP_SWIZZLE_64B : CU_TENSOR_MAP_SWIZZLE_NONE, CU_TENSOR_MAP_L2_PROMOTION_L2_256B, CU_TENSOR_MAP_FLOAT_OOB_FILL_NONE);
}
static void make_map3(CUtensorMap* m, const void* p, int rows, int cols, int box_rows, int box_chunks) {
    cuuint64_t dims[3] = {64, (cuuint64_t)rows, (cuuint64_t)cols / 64}, strides[2] = {(cuuint64_t)cols * 2, 128};
    cuuint32_t box[3] = {64, (cuuint32_t)box_rows, (cuuint32_t)box_chunks}, es[3] = {1, 1, 1};
    s_encode(m, CU_TENSOR_MAP_DATA_TYPE_BFLOAT16, 3, (void*)p, dims, strides, box, es, CU_TENSOR_MAP_INTERLEAVE_NONE,
             CU_TENSOR_MAP_SWIZZLE_128B, CU_TENSOR_MAP_L2_PROMOTION_L2_256B, CU_TENSOR_MAP_FLOAT_OOB_FILL_NONE);
}
template <typename T> static void* sym(T& s) { void* p = nullptr; cudaGetSymbolAddress(&p, s); return p; }

static void make_map_ln(CUtensorMap* m, const void* p, int ls) {
    cuuint64_t dims[4] = {128, 5, 128, NSLAB}, strides[3] = {256, DM * 2, 128 * DM * 2};
    cuuint32_t box[4] = {128, 5, (cuuint32_t)(32 >> ls), (cuuint32_t)(1 << ls)}, es[4] = {1, 1, 1, 1};
    s_encode(m, CU_TENSOR_MAP_DATA_TYPE_BFLOAT16, 4, (void*)p, dims, strides, box, es, CU_TENSOR_MAP_INTERLEAVE_NONE,
             CU_TENSOR_MAP_SWIZZLE_NONE, CU_TENSOR_MAP_L2_PROMOTION_L2_256B, CU_TENSOR_MAP_FLOAT_OOB_FILL_NONE);
}
static void make_sched(Sched* sd, const char* order, const char* lsplit, const char* lnst) {
    int slab = 0, end = 0;
    for (int b = 0; b < 16; b++) { sd->lsplit[b] = lsplit[b] - '0'; sd->lnst[b] = lnst[b] - '0'; sd->slab[b] = slab; slab += 1 << sd->lsplit[b]; }
    for (int r = 0; r < 64; r++) {
        const char k = order[2 * r], c = order[2 * r + 1]; const int b = c <= '9' ? c - '0' : c - 'a' + 10;
        sd->kind[r] = k == 'V' ? 0 : k == 'A' ? 1 : k == 'O' ? 2 : 3; sd->block[r] = b;
        end += k == 'O' ? 2 << sd->lsplit[b] : k == 'L' ? (4 << sd->lsplit[b]) / sd->lnst[b] : 32;
        sd->end[r] = end;
    }
}

extern "C" void kernel_launch(void* const* d_in, const int* in_sizes, int n_in, void* d_out, int out_size) {
    const bf16 *x = (const bf16*)d_in[0], *mem0 = (const bf16*)d_in[1], *Wq = (const bf16*)d_in[2], *Wk = (const bf16*)d_in[3],
               *Wv = (const bf16*)d_in[4], *Wo = (const bf16*)d_in[5], *wr = (const bf16*)d_in[8], *wgate = (const bf16*)d_in[9],
               *wup = (const bf16*)d_in[10], *wdown = (const bf16*)d_in[11], *c = (const bf16*)d_in[12], *wmod = (const bf16*)d_in[13];
    bf16* out = (bf16*)d_out;
    if (!s_encode) {
        cudaDriverEntryPointQueryResult qr;
        cudaGetDriverEntryPoint("cuTensorMapEncodeTiled", (void**)&s_encode, cudaEnableDefault, &qr);
        cudaFuncSetAttribute(k_side, cudaFuncAttributeMaxDynamicSharedMemorySize, SD_SMEM);
        cudaFuncSetAttribute(k_chain, cudaFuncAttributeMaxDynamicSharedMemorySize, C_SMEM);
    }
    ChainMaps cm; SideMaps sd; Sched sc;
    make_map(&sd.h, sym(g_h), S_TOK, DM, 128); make_map3(&sd.wv, Wv, DM, HD, 64, 3);
    make_map3(&sd.ost, sym(g_o), S_TOK, HD, 64, 3); make_map(&sd.o, sym(g_o), S_TOK, HD, 128, 32); make_map3(&sd.wo, Wo, HD, DM, 32, 5);
    make_map3(&sd.slab3, sym(g_slab), NSLAB * 128, DM, 64, 3); make_map3(&sd.slab2, sym(g_slab), NSLAB * 128, DM, 64, 2);
    for (int i = 0; i < 4; i++) make_map_ln(&sd.ln[i], sym(g_slab), i + 2);
    make_map(&sd.wgate, wgate, DM, FF, 128, 16); make_map(&sd.wup, wup, DM, FF, 128, 16); make_map(&sd.wdown, wdown, FF, DM, 256, 8);
    make_map(&cm.wq, Wq, DM, HD, 64); make_map(&cm.wk, Wk, DM, HD, 64); make_map(&cm.wv, Wv, DM, HD, 64); make_map(&cm.wo, Wo, HD, DM, 64, 32);
    make_map3(&cm.h1, sym(g_h), S_TOK, DM, 32, 1); make_map3(&cm.h4, sym(g_h), S_TOK, DM, 32, 4);
    make_map(&cm.wmod, wmod, DM, 6 * DM, 160, 48);
    ChainArgs ar = {x, mem0, c, Wv, Wo, 550, 0};
    const char *order = "V0V1V2V3V4A0V5O0A1V6O1A2V7O2L0A3V8O3L1A4V9O4L2A5VaO5L3A6VbO6L4A7VcO7L5A8VdO8L6A9VeO9L7AaVfOaL8AbL9AcObLaAdOcAeLbOdAfLcOeOfLdLeLf",
               *lsplit = "2222222222333445", *lnst = "2222222222222221";
    make_sched(&sc, order, lsplit, lnst);
    k_chain<<<96, 384, C_SMEM>>>(cm, ar);
    cudaLaunchConfig_t cfg = {};
    cfg.gridDim = dim3(N_SIDE); cfg.blockDim = dim3(384); cfg.dynamicSmemBytes = SD_SMEM; cfg.stream = cudaStreamPerThread;
    cudaLaunchAttribute at[1]; at[0].id = cudaLaunchAttributeProgrammaticStreamSerialization; at[0].val.programmaticStreamSerializationAllowed = 1;
    cfg.attrs = at; cfg.numAttrs = 1;
    cudaLaunchKernelEx(&cfg, k_side, sd, sc, x, wr, out);
}
```

```cpp
#include <cuda_runtime.h>
#include <cuda_bf16.h>
#include <cuda.h>
#include <stdint.h>
#include <stdio.h>
#include <string.h>
#include <stdlib.h>

typedef __nv_bfloat16 bf16;
constexpr int S_TOK = 2048, DM = 640, NH = 32, DH = 192, HD = NH * DH, NSEG = 64, SEG = 32, FF = 1536;

__device__ bf16 g_mod[6 * DM];
__device__ __align__(128) uint32_t g_modt[2 * DM];
__device__ bf16 g_h[S_TOK * DM];
constexpr int REC = 43008, R_Q = 12288, R_K = R_Q + 4096, R_KM = R_Q + 8192, R_VM = R_Q + 9216, R_J = 10240;
__device__ __align__(1024) uint8_t g_rec[(size_t)NSEG * NH * REC];
__host__ __device__ constexpr uint32_t vswz(uint32_t t) { return (t ^ (t >> 3 << 1)) & 7; }
__device__ bf16 g_o[S_TOK * HD];
__device__ bf16 g_x1[S_TOK * DM];
__device__ bf16 g_h2[S_TOK * DM];
__device__ bf16 g_r[S_TOK];
__device__ __align__(128) uint32_t g_gu[FF / 8 * 32];
__device__ __align__(1024) uint8_t g_acc[32 * 32768];
__device__ float g_slow[2 * NH * 20 * 32 * 8];
constexpr int NSLAB = 192;
__device__ bf16 g_slab[NSLAB * 128 * DM];
struct __align__(128) Flags {
    uint32_t v[16 * 32];
    uint32_t seg[64 * 32];
    uint32_t at[16 * 32];
    uint32_t o[16 * 32];
    uint32_t ln[16 * 32];
    uint32_t gu, pad1[31], slow, mod, pad3[30], anext, pad6[31], bnext, pad7[31];
    uint32_t h, pad4[31], done, pad5[31], next, pad2[31];
};
__device__ Flags g_flags;

__device__ __forceinline__ uint32_t smem_u32(const void* p) { return (uint32_t)__cvta_generic_to_shared(p); }
__device__ __forceinline__ uint32_t pack2(float lo, float hi) {
    uint32_t r; asm("cvt.rn.bf16x2.f32 %0, %1, %2;" : "=r"(r) : "f"(hi), "f"(lo)); return r;
}
__device__ __forceinline__ float bfr(float x) { return __uint_as_float(pack2(0.f, x)); }
__device__ __forceinline__ float inv_std(float var) {
    float s, r; asm("sqrt.approx.f32 %0, %1;" : "=f"(s) : "f"(bfr(bfr(var) + 1e-5f))); asm("rcp.approx.f32 %0, %1;" : "=f"(r) : "f"(bfr(s))); return r;
}
__device__ __forceinline__ float lo_f(uint32_t v) { return __uint_as_float(v << 16); }
__device__ __forceinline__ float hi_f(uint32_t v) { return __uint_as_float(v & 0xffff0000u); }
__device__ __forceinline__ void mbar_init(uint32_t bar, int cnt) { asm volatile("mbarrier.init.shared::cta.b64 [%0], %1;" :: "r"(bar), "r"(cnt) : "memory"); }
__device__ __forceinline__ void mbar_expect(uint32_t bar, int bytes) { asm volatile("mbarrier.arrive.expect_tx.shared::cta.b64 _, [%0], %1;" :: "r"(bar), "r"(bytes) : "memory"); }
__device__ __forceinline__ void mbar_arrive(uint32_t bar) { asm volatile("mbarrier.arrive.shared::cta.b64 _, [%0];" :: "r"(bar) : "memory"); }
constexpr int SPIN_LIMIT = 1 << 18;
__device__ __forceinline__ void mbar_wait(uint32_t bar, uint32_t par) {
    asm volatile("{ .reg .pred p, q; .reg .u32 n; mov.u32 n, 0;\n"
                 "W_%=: mbarrier.try_wait.parity.shared::cta.b64 p, [%0], %1;\n"
                 "@p bra.uni D_%=;\n"
                 "add.u32 n, n, 1; setp.lt.u32 q, n, 0x200000; @q bra.uni W_%=;\n"
                 "trap;\n"
                 "D_%=: }" :: "r"(bar), "r"(par) : "memory");
}
__device__ __forceinline__ bool mbar_test(uint32_t bar, uint32_t par) {
    uint32_t ok; asm volatile("{ .reg .pred p; mbarrier.test_wait.parity.shared::cta.b64 p, [%1], %2; selp.u32 %0, 1, 0, p; }" : "=r"(ok) : "r"(bar), "r"(par) : "memory"); return ok;
}
__device__ __forceinline__ void tma2d(uint32_t dst, const CUtensorMap* m, int c0, int c1, uint32_t bar) {
    asm volatile("cp.async.bulk.tensor.2d.shared::cluster.global.mbarrier::complete_tx::bytes [%0], [%1, {%3, %4}], [%2];"
        :: "r"(dst), "l"((uint64_t)m), "r"(bar), "r"(c0), "r"(c1) : "memory");
}
__device__ __forceinline__ uint64_t policy_stream() { uint64_t p; asm("createpolicy.fractional.L2::evict_first.b64 %0, 1.0;" : "=l"(p)); return p; }
__device__ __forceinline__ void tma2d_ef(uint32_t dst, const CUtensorMap* m, int c0, int c1, uint32_t bar, uint64_t pol) {
    asm volatile("cp.async.bulk.tensor.2d.shared::cluster.global.mbarrier::complete_tx::bytes.L2::cache_hint [%0], [%1, {%3, %4}], [%2], %5;"
        :: "r"(dst), "l"((uint64_t)m), "r"(bar), "r"(c0), "r"(c1), "l"(pol) : "memory");
}
__device__ __forceinline__ void tma3d(uint32_t dst, const CUtensorMap* m, int row, int chunk, uint32_t bar) {
    asm volatile("cp.async.bulk.tensor.3d.shared::cluster.global.mbarrier::complete_tx::bytes [%0], [%1, {0, %3, %4}], [%2];"
        :: "r"(dst), "l"((uint64_t)m), "r"(bar), "r"(row), "r"(chunk) : "memory");
}
__device__ __forceinline__ void tma3d_store(const CUtensorMap* m, int row, int chunk, uint32_t src, uint64_t pol, bool hint) {
    if (hint) asm volatile("cp.async.bulk.tensor.3d.global.shared::cta.bulk_group.L2::cache_hint [%0, {0, %2, %3}], [%1], %4;"
        :: "l"((uint64_t)m), "r"(src), "r"(row), "r"(chunk), "l"(pol) : "memory");
    else asm volatile("cp.async.bulk.tensor.3d.global.shared::cta.bulk_group [%0, {0, %2, %3}], [%1];"
        :: "l"((uint64_t)m), "r"(src), "r"(row), "r"(chunk) : "memory");
}
__device__ __forceinline__ bool elect() { uint32_t p; asm volatile("{ .reg .pred e; elect.sync _|e, -1; selp.u32 %0, 1, 0, e; }" : "=r"(p)); return p; }
__device__ __forceinline__ uint2 ld_ef(const void* p, uint64_t pol) {
    uint2 v; asm volatile("ld.relaxed.gpu.global.L2::cache_hint.v2.u32 {%0,%1}, [%2], %3;" : "=r"(v.x), "=r"(v.y) : "l"(p), "l"(pol)); return v;
}
__device__ __forceinline__ void st_ef(void* p, uint2 v, uint64_t pol) {
    asm volatile("st.global.L2::cache_hint.v2.u32 [%0], {%1,%2}, %3;" :: "l"(p), "r"(v.x), "r"(v.y), "l"(pol) : "memory");
}
__device__ __forceinline__ void bulk_g2s(uint32_t dst, const void* src, int bytes, uint32_t bar) {
    asm volatile("cp.async.bulk.shared::cluster.global.mbarrier::complete_tx::bytes [%0], [%1], %2, [%3];" :: "r"(dst), "l"(src), "r"(bytes), "r"(bar) : "memory");
}
__device__ __forceinline__ void bulk_g2s_ef(uint32_t dst, const void* src, int bytes, uint32_t bar, uint64_t pol) {
    asm volatile("cp.async.bulk.shared::cluster.global.mbarrier::complete_tx::bytes.L2::cache_hint [%0], [%1], %2, [%3], %4;" :: "r"(dst), "l"(src), "r"(bytes), "r"(bar), "l"(pol) : "memory");
}
__device__ __forceinline__ void bulk_s2g(void* dst, uint32_t src, int bytes) {
    asm volatile("cp.async.bulk.global.shared::cta.bulk_group [%0], [%1], %2;" :: "l"(dst), "r"(src), "r"(bytes) : "memory");
}
__device__ __forceinline__ void bulk_s2g_ef(void* dst, uint32_t src, int bytes, uint64_t pol) {
    asm volatile("cp.async.bulk.global.shared::cta.bulk_group.L2::cache_hint [%0], [%1], %2, %3;" :: "l"(dst), "r"(src), "r"(bytes), "l"(pol) : "memory");
}
#define EF 31
#define BULK_COMMIT()    asm volatile("cp.async.bulk.commit_group;" ::: "memory")
#define BULK_WAIT_READ() asm volatile("cp.async.bulk.wait_group.read 0;" ::: "memory")
#define BULK_WAIT()      asm volatile("cp.async.bulk.wait_group 0;" ::: "memory")
#define PROXY_FENCE()    asm volatile("fence.proxy.async.shared::cta;" ::: "memory")
__device__ __forceinline__ void ldsm4(uint32_t (&r)[4], uint32_t a) {
    asm volatile("ldmatrix.sync.aligned.m8n8.x4.shared.b16 {%0,%1,%2,%3}, [%4];" : "=r"(r[0]), "=r"(r[1]), "=r"(r[2]), "=r"(r[3]) : "r"(a) : "memory");
}
__device__ __forceinline__ void ldsm4t(uint32_t (&r)[4], uint32_t a) {
    asm volatile("ldmatrix.sync.aligned.m8n8.x4.trans.shared.b16 {%0,%1,%2,%3}, [%4];" : "=r"(r[0]), "=r"(r[1]), "=r"(r[2]), "=r"(r[3]) : "r"(a) : "memory");
}
__device__ __forceinline__ void stsm4(uint32_t a, uint32_t r0, uint32_t r1, uint32_t r2, uint32_t r3) {
    asm volatile("stmatrix.sync.aligned.m8n8.x4.shared.b16 [%0], {%1,%2,%3,%4};" :: "r"(a), "r"(r0), "r"(r1), "r"(r2), "r"(r3) : "memory");
}
__device__ __forceinline__ uint32_t movm_t(uint32_t v) { uint32_t r; asm volatile("movmatrix.sync.aligned.m8n8.trans.b16 %0, %1;" : "=r"(r) : "r"(v)); return r; }
__device__ __forceinline__ void mma16(float (&d)[4], uint32_t a0, uint32_t a1, uint32_t a2, uint32_t a3, uint32_t b0, uint32_t b1) {
    asm volatile("mma.sync.aligned.m16n8k16.row.col.f32.bf16.bf16.f32 {%0,%1,%2,%3}, {%4,%5,%6,%7}, {%8,%9}, {%0,%1,%2,%3};"
        : "+f"(d[0]), "+f"(d[1]), "+f"(d[2]), "+f"(d[3]) : "r"(a0), "r"(a1), "r"(a2), "r"(a3), "r"(b0), "r"(b1));
}
__device__ __forceinline__ void mma16(float (&d)[4], const uint32_t (&a)[4], uint32_t b0, uint32_t b1) { mma16(d, a[0], a[1], a[2], a[3], b0, b1); }
__device__ __forceinline__ void mma16z(float (&d)[4], const uint32_t (&a)[4], uint32_t b0, uint32_t b1) {
    asm volatile("mma.sync.aligned.m16n8k16.row.col.f32.bf16.bf16.f32 {%0,%1,%2,%3}, {%4,%5,%6,%7}, {%8,%9}, {%10,%10,%10,%10};"
        : "=f"(d[0]), "=f"(d[1]), "=f"(d[2]), "=f"(d[3]) : "r"(a[0]), "r"(a[1]), "r"(a[2]), "r"(a[3]), "r"(b0), "r"(b1), "f"(0.f));
}
__device__ __forceinline__ void mma8z(float (&d)[4], uint32_t a0, uint32_t a1, uint32_t b0) {
    asm volatile("mma.sync.aligned.m16n8k8.row.col.f32.bf16.bf16.f32 {%0,%1,%2,%3}, {%4,%5}, {%6}, {%7,%7,%7,%7};"
        : "=f"(d[0]), "=f"(d[1]), "=f"(d[2]), "=f"(d[3]) : "r"(a0), "r"(a1), "r"(b0), "f"(0.f));
}
__device__ __forceinline__ void bar_sync(int id, int n) { asm volatile("bar.sync %0, %1;" :: "r"(id), "r"(n) : "memory"); }
__device__ __forceinline__ void bar_arrive(int id, int n) { asm volatile("bar.arrive %0, %1;" :: "r"(id), "r"(n) : "memory"); }
__device__ __forceinline__ uint64_t mkdesc(uint32_t addr, uint32_t lbo, uint32_t sbo) {
    return (uint64_t)((addr & 0x3FFFF) >> 4) | ((uint64_t)(lbo >> 4) << 16) | ((uint64_t)(sbo >> 4) << 32) | (1ull << 62);
}
#define WG_FENCE()  asm volatile("wgmma.fence.sync.aligned;" ::: "memory")
#define WG_COMMIT() asm volatile("wgmma.commit_group.sync.aligned;" ::: "memory")
#define WG_WAIT(n)  asm volatile("wgmma.wait_group.sync.aligned %0;" :: "n"(n) : "memory")

__device__ __forceinline__ void wgmma_ss_n192_tb(float (&d)[96], uint64_t a, uint64_t b, int acc) {
    asm volatile("{ .reg .pred p; setp.ne.b32 p, %98, 0;\n"
        "wgmma.mma_async.sync.aligned.m64n192k16.f32.bf16.bf16 {%0,%1,%2,%3,%4,%5,%6,%7,%8,%9,%10,%11,%12,%13,%14,%15,%16,%17,%18,%19,%20,%21,%22,%23,%24,%25,%26,%27,%28,%29,%30,%31,%32,%33,%34,%35,%36,%37,%38,%39,%40,%41,%42,%43,%44,%45,%46,%47,%48,%49,%50,%51,%52,%53,%54,%55,%56,%57,%58,%59,%60,%61,%62,%63,%64,%65,%66,%67,%68,%69,%70,%71,%72,%73,%74,%75,%76,%77,%78,%79,%80,%81,%82,%83,%84,%85,%86,%87,%88,%89,%90,%91,%92,%93,%94,%95}, %96, %97, p, 1, 1, 0, 1; }"
        : "+f"(d[0]), "+f"(d[1]), "+f"(d[2]), "+f"(d[3]), "+f"(d[4]), "+f"(d[5]), "+f"(d[6]), "+f"(d[7]), "+f"(d[8]), "+f"(d[9]), "+f"(d[10]), "+f"(d[11]), "+f"(d[12]), "+f"(d[13]), "+f"(d[14]), "+f"(d[15]), "+f"(d[16]), "+f"(d[17]), "+f"(d[18]), "+f"(d[19]), "+f"(d[20]), "+f"(d[21]), "+f"(d[22]), "+f"(d[23]), "+f"(d[24]), "+f"(d[25]), "+f"(d[26]), "+f"(d[27]), "+f"(d[28]), "+f"(d[29]), "+f"(d[30]), "+f"(d[31]), "+f"(d[32]), "+f"(d[33]), "+f"(d[34]), "+f"(d[35]), "+f"(d[36]), "+f"(d[37]), "+f"(d[38]), "+f"(d[39]), "+f"(d[40]), "+f"(d[41]), "+f"(d[42]), "+f"(d[43]), "+f"(d[44]), "+f"(d[45]), "+f"(d[46]), "+f"(d[47]), "+f"(d[48]), "+f"(d[49]), "+f"(d[50]), "+f"(d[51]), "+f"(d[52]), "+f"(d[53]), "+f"(d[54]), "+f"(d[55]), "+f"(d[56]), "+f"(d[57]), "+f"(d[58]), "+f"(d[59]), "+f"(d[60]), "+f"(d[61]), "+f"(d[62]), "+f"(d[63]), "+f"(d[64]), "+f"(d[65]), "+f"(d[66]), "+f"(d[67]), "+f"(d[68]), "+f"(d[69]), "+f"(d[70]), "+f"(d[71]), "+f"(d[72]), "+f"(d[73]), "+f"(d[74]), "+f"(d[75]), "+f"(d[76]), "+f"(d[77]), "+f"(d[78]), "+f"(d[79]), "+f"(d[80]), "+f"(d[81]), "+f"(d[82]), "+f"(d[83]), "+f"(d[84]), "+f"(d[85]), "+f"(d[86]), "+f"(d[87]), "+f"(d[88]), "+f"(d[89]), "+f"(d[90]), "+f"(d[91]), "+f"(d[92]), "+f"(d[93]), "+f"(d[94]), "+f"(d[95])
        : "l"(a), "l"(b), "r"(acc));
}

__device__ __forceinline__ void wgmma_ss_n128_tb(float (&d)[64], uint64_t a, uint64_t b, int acc) {
    asm volatile("{ .reg .pred p; setp.ne.b32 p, %66, 0;\n"
        "wgmma.mma_async.sync.aligned.m64n128k16.f32.bf16.bf16 {%0,%1,%2,%3,%4,%5,%6,%7,%8,%9,%10,%11,%12,%13,%14,%15,%16,%17,%18,%19,%20,%21,%22,%23,%24,%25,%26,%27,%28,%29,%30,%31,%32,%33,%34,%35,%36,%37,%38,%39,%40,%41,%42,%43,%44,%45,%46,%47,%48,%49,%50,%51,%52,%53,%54,%55,%56,%57,%58,%59,%60,%61,%62,%63}, %64, %65, p, 1, 1, 0, 1; }"
        : "+f"(d[0]), "+f"(d[1]), "+f"(d[2]), "+f"(d[3]), "+f"(d[4]), "+f"(d[5]), "+f"(d[6]), "+f"(d[7]), "+f"(d[8]), "+f"(d[9]), "+f"(d[10]), "+f"(d[11]), "+f"(d[12]), "+f"(d[13]), "+f"(d[14]), "+f"(d[15]), "+f"(d[16]), "+f"(d[17]), "+f"(d[18]), "+f"(d[19]), "+f"(d[20]), "+f"(d[21]), "+f"(d[22]), "+f"(d[23]), "+f"(d[24]), "+f"(d[25]), "+f"(d[26]), "+f"(d[27]), "+f"(d[28]), "+f"(d[29]), "+f"(d[30]), "+f"(d[31]), "+f"(d[32]), "+f"(d[33]), "+f"(d[34]), "+f"(d[35]), "+f"(d[36]), "+f"(d[37]), "+f"(d[38]), "+f"(d[39]), "+f"(d[40]), "+f"(d[41]), "+f"(d[42]), "+f"(d[43]), "+f"(d[44]), "+f"(d[45]), "+f"(d[46]), "+f"(d[47]), "+f"(d[48]), "+f"(d[49]), "+f"(d[50]), "+f"(d[51]), "+f"(d[52]), "+f"(d[53]), "+f"(d[54]), "+f"(d[55]), "+f"(d[56]), "+f"(d[57]), "+f"(d[58]), "+f"(d[59]), "+f"(d[60]), "+f"(d[61]), "+f"(d[62]), "+f"(d[63])
        : "l"(a), "l"(b), "r"(acc));
}

__device__ __forceinline__ void wgmma_rs_n32(float (&d)[16], const uint32_t (&a)[4], uint64_t b) {
    asm volatile("wgmma.mma_async.sync.aligned.m64n32k16.f32.bf16.bf16 {%0,%1,%2,%3,%4,%5,%6,%7,%8,%9,%10,%11,%12,%13,%14,%15}, {%16,%17,%18,%19}, %20, 1, 1, 1, 0;"
        : "+f"(d[0]), "+f"(d[1]), "+f"(d[2]), "+f"(d[3]), "+f"(d[4]), "+f"(d[5]), "+f"(d[6]), "+f"(d[7]), "+f"(d[8]), "+f"(d[9]), "+f"(d[10]), "+f"(d[11]), "+f"(d[12]), "+f"(d[13]), "+f"(d[14]), "+f"(d[15])
        : "r"(a[0]), "r"(a[1]), "r"(a[2]), "r"(a[3]), "l"(b));
}
__device__ __forceinline__ uint32_t umax3(uint32_t a, uint32_t b, uint32_t c) { return max(max(a, b), c); }
__device__ __forceinline__ void wait_until(uint32_t t) { while ((int32_t)((uint32_t)clock() - t) < 0) {} }
__device__ __forceinline__ uint32_t gtime() { uint32_t c; asm volatile("mov.u32 %0, %%globaltimer_lo;" : "=r"(c)); return c; }
__device__ __forceinline__ uint32_t opaque(uint32_t v) { uint32_t r; asm volatile("shfl.sync.bfly.b32 %0, %1, 0, 31, -1;" : "=r"(r) : "r"(v)); return r; }
__device__ __forceinline__ uint32_t lds32(uint32_t a) { uint32_t v; asm volatile("ld.shared.u32 %0, [%1];" : "=r"(v) : "r"(a) : "memory"); return v; }
__device__ __forceinline__ void sts32(uint32_t a, uint32_t v) { asm volatile("st.shared.u32 [%0], %1;" :: "r"(a), "r"(v) : "memory"); }
__device__ __forceinline__ void lds64(uint32_t (&v)[2], uint32_t a) { asm volatile("ld.shared.v2.u32 {%0,%1}, [%2];" : "=r"(v[0]), "=r"(v[1]) : "r"(a) : "memory"); }
__device__ __forceinline__ void lds128(uint32_t (&v)[4], uint32_t a) { asm volatile("ld.shared.v4.u32 {%0,%1,%2,%3}, [%4];" : "=r"(v[0]), "=r"(v[1]), "=r"(v[2]), "=r"(v[3]) : "r"(a) : "memory"); }
__device__ __forceinline__ void sts128(uint32_t a, uint32_t x, uint32_t y, uint32_t z, uint32_t w) { asm volatile("st.shared.v4.u32 [%0], {%1,%2,%3,%4};" :: "r"(a), "r"(x), "r"(y), "r"(z), "r"(w) : "memory"); }
__device__ __forceinline__ float2 lds64f(uint32_t a) { float2 v; asm volatile("ld.shared.v2.f32 {%0,%1}, [%2];" : "=f"(v.x), "=f"(v.y) : "r"(a) : "memory"); return v; }
__device__ __forceinline__ float4 lds128f(uint32_t a) { float4 v; asm volatile("ld.shared.v4.f32 {%0,%1,%2,%3}, [%4];" : "=f"(v.x), "=f"(v.y), "=f"(v.z), "=f"(v.w) : "r"(a) : "memory"); return v; }
__device__ __forceinline__ void sts128f(uint32_t a, float x, float y, float z, float w) { asm volatile("st.shared.v4.f32 [%0], {%1,%2,%3,%4};" :: "r"(a), "f"(x), "f"(y), "f"(z), "f"(w) : "memory"); }

__device__ __forceinline__ float warp_sum(float v) {
#pragma unroll
    for (int o = 16; o; o >>= 1) v += __shfl_xor_sync(0xffffffffu, v, o);
    return v;
}
__device__ __forceinline__ uint32_t badd(uint32_t a, uint32_t b) { uint32_t r; asm("add.rn.bf16x2 %0, %1, %2;" : "=r"(r) : "r"(a), "r"(b)); return r; }
__device__ __forceinline__ uint32_t bsub(uint32_t a, uint32_t b) { uint32_t r; asm("sub.rn.bf16x2 %0, %1, %2;" : "=r"(r) : "r"(a), "r"(b)); return r; }
__device__ __forceinline__ uint32_t bmul(uint32_t a, uint32_t b) { uint32_t r; asm("mul.rn.bf16x2 %0, %1, %2;" : "=r"(r) : "r"(a), "r"(b)); return r; }
__device__ __forceinline__ uint32_t silu2(uint32_t v) { return pack2(__fdividef(lo_f(v), 1.f + __expf(-lo_f(v))), __fdividef(hi_f(v), 1.f + __expf(-hi_f(v)))); }
__device__ __forceinline__ void ln_row(const uint32_t (&x)[10], uint32_t (&n)[10]) {
    float s0 = 0, s1 = 0;
#pragma unroll
    for (int i = 0; i < 10; i++) { s0 += lo_f(x[i]); s1 += hi_f(x[i]); }
    const float mean = warp_sum(s0 + s1) * (1.f / DM);
    float q0 = 0, q1 = 0;
#pragma unroll
    for (int i = 0; i < 10; i++) { const float d0 = lo_f(x[i]) - mean, d1 = hi_f(x[i]) - mean; q0 += d0 * d0; q1 += d1 * d1; }
    const uint32_t mb = pack2(mean, mean);
    const float inv = inv_std(warp_sum(q0 + q1) * (1.f / DM));
#pragma unroll
    for (int i = 0; i < 10; i++) { const uint32_t d = bsub(x[i], mb); n[i] = pack2(lo_f(d) * inv, hi_f(d) * inv); }
}
__device__ __forceinline__ uint32_t ld_rlx(const uint32_t* f) { uint32_t v; asm volatile("ld.relaxed.gpu.global.u32 %0, [%1];" : "=r"(v) : "l"(f) : "memory"); return v; }
__device__ __forceinline__ void bump(uint32_t* f) { asm volatile("red.relaxed.gpu.global.add.u32 [%0], 1;" :: "l"(f) : "memory"); }
__device__ __forceinline__ void flag_wait(const uint32_t* f, uint32_t target) {
    for (int n = 0;; n++) {
        uint32_t v; asm volatile("ld.relaxed.gpu.global.u32 %0, [%1];" : "=r"(v) : "l"(f) : "memory");
        if (v >= target) break;
        if (n > (1 << 23)) __trap();
    }
}
__device__ __forceinline__ void flag_wait_warp(const uint32_t* f, uint32_t target) {
    for (int n = 0; !__all_sync(0xffffffffu, ld_rlx(f) >= target); n++) if (n > (1 << 23)) __trap();
}
__device__ __forceinline__ void flag_add(uint32_t* f, uint32_t v = 1) { asm volatile("red.release.gpu.global.add.u32 [%0], %1;" :: "l"(f), "r"(v) : "memory"); }
constexpr int N_SIDE = 132;
__device__ __forceinline__ void flags_release() {
    uint32_t old; asm volatile("atom.acq_rel.gpu.global.add.u32 %0, [%1], 1;" : "=r"(old) : "l"(&g_flags.done) : "memory");
    if (old == 96 + N_SIDE - 1) { g_flags.h = 0; g_flags.next = 0; g_flags.done = 0; }
}

struct ChainMaps { CUtensorMap wq, wk, wv, wo, h1, h4, wmod; };
struct ChainArgs { const bf16 *x, *mem0, *c; int D, D2, force, P[4]; };
constexpr uint32_t SM_BASE = 1024;
constexpr int C_WV = 0, C_WO = 81920, C_XR = 167936, C_QX = C_XR + 4 * 4096, C_KX = C_XR + 9 * 4096, C_VX = C_XR + 40960, C_MEM = C_VX + 4096, C_VP = C_MEM,
              C_QM = C_MEM + 10240, C_KM = C_QM + 1024, C_VM = C_KM + 1024, C_OX = C_VM + 1024, C_SC = C_OX + 3072, C_BAR = C_SC + 1920, C_SMEM = C_BAR + 256;
constexpr int CB_W = C_BAR, CB_W2 = C_BAR + 8, CB_SC = C_BAR + 16, CB_OX = C_BAR + 24, CB_VX = C_BAR + 32, CB_XF = C_BAR + 40, CB_XG = C_BAR + 48, CB_PRE = C_BAR + 56, CB_WK = C_BAR + 64, CB_PC = C_BAR + 96,
              C_MAX = C_BAR + 128, C_SCL = C_BAR + 144, C_BAD = C_BAR + 148;
static_assert(C_SMEM <= 232448, "chain shared memory");
enum { B_MEM = 1, B_QK, B_VP, B_OWN, B_RED, B_X, B_AUX, B_VM };
constexpr int NP = 8;
constexpr int NW = 8;
#define VD 2
#define VPB 4
#define VPRE 1
#define BX 3
constexpr int OD = 4;
#define PROF(i)
#define PROFG(i)
#define PROFV(i, v)
#define SFENCE() asm volatile("griddepcontrol.launch_dependents;" ::: "memory")
#define PIN(x) asm volatile("" : "+r"(x))
#define PINL(x) asm volatile("" : "+l"(x))
__host__ __device__ constexpr bool pair_v(int i) { return i == 0 || (i % 3 == 2 && i < 9); }
__host__ __device__ constexpr bool pair_own(int i) { return pair_v(i) || i >= 14; }
__host__ __device__ constexpr int pair_idx(int i) { return pair_v(i) ? (i + 1) / 3 : i < 14 ? i - (i < 9 ? i / 3 + 1 : 4) : i - 10; }
__host__ __device__ constexpr int pair_ld(int i) { return i + 2 + (i / 3 < BX ? i / 3 : BX) < 20 ? i + 2 + (i / 3 < BX ? i / 3 : BX) : 20; }

__device__ __forceinline__ uint32_t packh(float lo, float hi) { uint32_t r; asm("cvt.rn.f16x2.f32 %0, %1, %2;" : "=r"(r) : "f"(hi), "f"(lo)); return r; }
__device__ __forceinline__ uint32_t h2b(uint32_t v) {
    uint32_t r; asm("{ .reg .f16 a, b; .reg .f32 x, y; mov.b32 {a, b}, %1; cvt.f32.f16 x, a; cvt.f32.f16 y, b; cvt.rn.bf16x2.f32 %0, y, x; }" : "=r"(r) : "r"(v)); return r;
}
__device__ __forceinline__ uint32_t h2b_lo(uint32_t u, uint32_t v) {
    uint32_t r; asm("{ .reg .f16 a, b, c, d; .reg .f32 x, y; mov.b32 {a, b}, %1; mov.b32 {c, d}, %2; cvt.f32.f16 x, a; cvt.f32.f16 y, c; cvt.rn.bf16x2.f32 %0, y, x; }" : "=r"(r) : "r"(u), "r"(v)); return r;
}
constexpr float SCL2E = 0.07216878364870322f * 1.4426950408889634f;
__device__ __forceinline__ uint32_t score_tile(const uint32_t (&qa)[2][4], const uint32_t (&kb)[2][4]) {
    float u[4], v[4], x[4], y[4];
    mma16z(u, qa[0], kb[0][0], kb[0][1]); mma16z(v, qa[0], kb[0][2], kb[0][3]);
    mma16z(x, qa[1], kb[1][0], kb[1][1]); mma16z(y, qa[1], kb[1][2], kb[1][3]);
    return pack2(((u[0] + v[2]) + (x[0] + y[2])) * SCL2E, ((u[1] + v[3]) + (x[1] + y[3])) * SCL2E);
}
__device__ __forceinline__ void score_tiles(const uint32_t (&qa)[2][4], const uint32_t (&kb)[2][4], const uint32_t (&km)[2][4], uint32_t& a, uint32_t& b) {
    float u[4], v[4], x[4], y[4];
    mma16z(u, qa[0], kb[0][0], kb[0][1]); mma16z(v, qa[0], kb[0][2], kb[0][3]); mma16z(x, qa[0], km[0][0], km[0][1]); mma16z(y, qa[0], km[0][2], km[0][3]);
    mma16(u, qa[1], kb[1][0], kb[1][1]); mma16(v, qa[1], kb[1][2], kb[1][3]); mma16(x, qa[1], km[1][0], km[1][1]); mma16(y, qa[1], km[1][2], km[1][3]);
    a = pack2((u[0] + v[2]) * SCL2E, (u[1] + v[3]) * SCL2E); b = pack2((x[0] + y[2]) * SCL2E, (x[1] + y[3]) * SCL2E);
}
__device__ __forceinline__ void stas1(uint32_t dst, uint32_t x, uint32_t bar) {
    asm volatile("st.async.shared::cluster.mbarrier::complete_tx::bytes.b32 [%0], %1, [%2];" :: "r"(dst), "r"(x), "r"(bar) : "memory");
}
__device__ __forceinline__ void stas2(uint32_t dst, uint32_t x, uint32_t y, uint32_t bar) {
    asm volatile("st.async.shared::cluster.mbarrier::complete_tx::bytes.v2.b32 [%0], {%1,%2}, [%3];" :: "r"(dst), "r"(x), "r"(y), "r"(bar) : "memory");
}
__device__ __forceinline__ float ex2(float x) { float r; asm volatile("ex2.approx.ftz.f32 %0, %1;" : "=f"(r) : "f"(x)); return r; }
__device__ __forceinline__ void h_fetch_a(const ChainMaps& mp, uint32_t sm, int n) {
    mbar_expect(sm + CB_XF, 32768);
    tma3d(sm + C_XR, &mp.h4, n * SEG, 0, sm + CB_XF); tma3d(sm + C_XR + 20480, &mp.h4, n * SEG, 5, sm + CB_XF);
}
__device__ __forceinline__ void h_fetch_b(const ChainMaps& mp, uint32_t sm, int n) {
    mbar_expect(sm + CB_XG, 8192);
    tma3d(sm + C_QX, &mp.h1, n * SEG, 4, sm + CB_XG); tma3d(sm + C_KX, &mp.h1, n * SEG, 9, sm + CB_XG);
}
__device__ __forceinline__ uint32_t absmax2(uint32_t a, uint32_t b) {
    uint32_t r; asm("max.u16x2 %0, %1, %2;" : "=r"(r) : "r"(a), "r"(b & 0x7fff7fffu)); return r;
}

__global__ void __cluster_dims__(3, 1, 1) __launch_bounds__(384, 1) k_chain(const __grid_constant__ ChainMaps mp, const __grid_constant__ ChainArgs ar) {
    extern __shared__ __align__(1024) uint8_t smraw[];
    const uint32_t sm = SM_BASE + ((blockIdx.x % 3) << 24);
    if (smem_u32(smraw) != sm) __trap();
    uint32_t tid; asm volatile("mov.u32 %0, %%tid.x;" : "=r"(tid));
    const int warp = __shfl_sync(0xffffffffu, tid >> 5, 0), lane = tid & 31, wg = warp >> 2, w = warp & 3;
    const int blk = blockIdx.x, head = blk / 3, j = blk % 3;
    const int col0 = head * DH + j * 64, u0 = 7 * j, nu = j == 2 ? 6 : 7;
    asm volatile("griddepcontrol.launch_dependents;");
#define PPROF(i)
#define PPROF2(i)
    PPROF(0);
    const int r = lane & 7, mi = lane >> 3;
    {
        if (warp == 11) {
            if (lane < 16) mbar_init(sm + C_BAR + 8 * lane, lane == 2 ? 5 : 1);
            asm volatile("fence.mbarrier_init.release.cluster;" ::: "memory");
            __syncwarp();
            if (elect()) {
                mbar_expect(sm + CB_PRE, (blk < 80 ? 20480 : 0) + 10240);
                if (blk < 80) {
#pragma unroll 1
                    for (int c = 0; c < 4; c++) tma2d(sm + C_XR + c * 5120, &mp.wmod, blk * 16, c * 160, sm + CB_PRE);
                }
                bulk_g2s(sm + C_XR + 20480, ar.mem0, 10240, sm + CB_PRE);
                mbar_expect(sm + CB_SC, 1280); mbar_expect(sm + CB_OX, 2048);
            }
            __syncwarp();
            asm volatile("barrier.cluster.arrive.relaxed.aligned; barrier.cluster.wait.aligned;" ::: "memory");
        } else {
        const int row0 = blk * 11 + warp; const bool two = row0 < S_TOK - 1056;
        uint32_t xv[2][10], cv[8];
#pragma unroll
        for (int i = 0; i < 8; i++) cv[i] = __ldg((const uint32_t*)ar.c + (warp < 10 ? warp : 0) * 32 + i * 4 + (lane & 3));
#pragma unroll
        for (int i = 0; i < 10; i++) {
            const uint2 v = __ldg((const uint2*)(ar.x + (row0 + (i >= 5 && two ? 1056 : 0)) * DM) + lane + i % 5 * 32);
            xv[i / 5][2 * (i % 5)] = v.x; xv[i / 5][2 * (i % 5) + 1] = v.y;
        }
        asm volatile("barrier.cluster.arrive.relaxed.aligned;" ::: "memory");
#pragma unroll 1
        for (int i = blk * 352 + tid; i < 32 * 1600; i += 96 * 352) ((uint4*)g_acc)[i / 1600 * 2048 + i % 1600] = make_uint4(0, 0, 0, 0);
        if (tid < 12 && blk * 12 + tid < (int)(offsetof(Flags, h) / 16)) ((uint4*)&g_flags)[blk * 12 + tid] = make_uint4(0, 0, 0, 0);
        static_assert(offsetof(Flags, h) <= 96 * 12 * 16, "flags");
        PPROF(8);
        asm volatile("barrier.cluster.wait.aligned;" ::: "memory");
        PPROF(9);
#pragma unroll
        for (int i = 0; i < 8; i++) cv[i] = silu2(cv[i]);
        mbar_wait(sm + CB_PRE, 0);
        PPROF(10);
        if (warp < 10) {
            float d[4] = {0, 0, 0, 0};
#pragma unroll
            for (int k = 0; k < 4; k++) { uint32_t a[4]; ldsm4t(a, sm + C_XR + ((warp * 4 + k) * 16 + (mi >> 1) * 8 + r) * 32 + (mi & 1) * 16); mma16(d, a, cv[2 * k], cv[2 * k + 1]); }
            if ((lane & 3) == 0) { sts32(sm + C_QM + warp * 64 + lane, __float_as_uint(d[0])); sts32(sm + C_QM + warp * 64 + 32 + lane, __float_as_uint(d[2])); }
        }
        bar_sync(B_MEM, 352);
        PPROF(11);
        if (tid < 16 && blk < 80) {
            float a = 0;
#pragma unroll
            for (int i = 0; i < 10; i++) a += __uint_as_float(lds32(sm + C_QM + i * 64 + tid * 4));
            asm volatile("st.relaxed.gpu.global.u32 [%0], %1;" :: "l"(g_modt + blk * 16 + tid), "r"(pack2(0.f, a) | 1u) : "memory");
        }
        PPROF(1);
#pragma unroll 1
        for (int q = 0; q < 2; q++) {
            uint32_t n[10]; ln_row(xv[0], n);
#pragma unroll
            for (int i = 0; i < 10; i++) { xv[0][i] = xv[1][i]; xv[1][i] = n[i]; }
        }
        if (tid < 320) {
            uint32_t v[4];
            for (int n = 0;; n++) {
                asm volatile("ld.relaxed.gpu.global.v4.u32 {%0,%1,%2,%3}, [%4];" : "=r"(v[0]), "=r"(v[1]), "=r"(v[2]), "=r"(v[3]) : "l"(g_modt + tid * 4) : "memory");
                if (__all_sync(0xffffffffu, v[0] & v[1] & v[2] & v[3] & 1)) break;
                if (n > (1 << 22)) __trap();
            }
            asm volatile("st.shared.v2.u32 [%0], {%1,%2};" :: "r"(sm + C_VX + tid * 8), "r"(__byte_perm(v[0], v[1], 0x7632)), "r"(__byte_perm(v[2], v[3], 0x7632)) : "memory");
        }
        bar_sync(B_MEM, 352);
        PPROF(2);
#pragma unroll
        for (int i = 0; i < 5; i++) {
            uint32_t sh[2], sc[2]; lds64(sh, sm + C_VX + lane * 8 + i * 256); lds64(sc, sm + C_VX + 1280 + lane * 8 + i * 256);
            sc[0] = badd(sc[0], 0x3f803f80u); sc[1] = badd(sc[1], 0x3f803f80u);
#pragma unroll
            for (int q = 0; q < 2; q++)
                if (q == 0 || two) ((uint2*)(g_h + (row0 + q * 1056) * DM))[lane + i * 32] = make_uint2(badd(bmul(xv[q][2 * i], sc[0]), sh[0]), badd(bmul(xv[q][2 * i + 1], sc[1]), sh[1]));
        }
        if (warp < 10) {
#pragma unroll
            for (int i = 0; i < 2; i++) {
                uint32_t v[4]; ldsm4t(v, sm + C_XR + 20480 + r * 1280 + ((warp * 2 + i) * 4 + mi) * 16);
                stsm4(sm + C_MEM + (warp * 2 + i) * 512 + lane * 16, v[0], v[1], v[2], v[3]);
            }
        }
        bar_sync(B_MEM, 352);
        PPROF(3);
        }
    }
    uint8_t* const rec0 = g_rec + (size_t)head * REC;
    if (wg < 2) {
        asm volatile("setmaxnreg.inc.sync.aligned.u32 224;");
        const uint32_t l16 = opaque(sm + lane * 16);
        uint32_t wa[40][4], pl[NP][4];
        const uint32_t wfrag = ((mi >> 1) * 8 + r) * 128 + (((2 * w + (mi & 1)) ^ r) << 4);
        mbar_wait(sm + (wg ? CB_WK : CB_W), 0);
#pragma unroll
        for (int i = 0; i < 40; i++)
            ldsm4t(wa[i], sm + (wg == 0 ? C_WV : C_WO) + wfrag + ((pair_own(i >> 1) ? wg : 1 - wg) * 20 + pair_idx(i >> 1) * 2 + (i & 1)) * 2048);
        PPROF(5);
        if (wg) bar_arrive(B_VM, 160); else bar_arrive(B_OWN, 160);
        const uint32_t wvrd = opaque(sm + C_WV + wfrag + wg * 40960);
        const uint32_t word = opaque(sm + C_WO + warp * 2048 + ((mi >> 1) * 8 + r) * 64 + (((mi & 1) ^ (r >> 1)) << 4));
        const uint32_t own = wg * 5120, oth = 5120 - own;
        mbar_wait(sm + CB_XF, 0);
#pragma unroll 1
        for (int s = -1;;) {
            uint64_t xo = mkdesc(SM_BASE + C_XR + wg * 20480, 16, 1024), xt = mkdesc(SM_BASE + C_XR + 20480 - wg * 20480, 16, 1024);
            if (s >= 0) {
                float dv[2][4], d[4][4], u[4], isc;
                uint32_t b[20][4], av[20][4], l4;
                const uint32_t mo = l16 + C_MEM + own, mt = l16 + C_MEM + oth;
                bar_sync(B_MEM, 384);
                if (warp == 0) { PROF(0); PROFG(24); }
#pragma unroll
                for (int i = 0; i < 20; i++) {
                    const int c = i < 3 ? 0 : (i & 1) * 2, p = 2 * pair_idx(i);
                    if (i) SFENCE();
#pragma unroll
                    for (int e = 0; e < 2; e++) { const int n = (i ? pair_ld(i - 1) : 0) + e; if (n < pair_ld(i)) ldsm4t(b[n], (pair_own(n) ? mo : mt) + pair_idx(n) * 512); }
                    if (i >= 18 - VPRE && i < 18) ldsm4t(av[NP + i - (18 - VPRE)], wvrd + (NP + i - (18 - VPRE)) * 2048);
                    if (i > 0 && pair_v(i)) { mma16(dv[0], pl[p % NP], b[i][0], b[i][1]); mma16(dv[1], pl[(p + 1) % NP], b[i][2], b[i][3]); }
                    if (i == 0 || i == 3) { mma16z(d[c], wa[2 * i], b[i][0], b[i][1]); mma16z(d[c + 1], wa[2 * i + 1], b[i][2], b[i][3]); }
                    else { mma16(d[c], wa[2 * i], b[i][0], b[i][1]); mma16(d[c + 1], wa[2 * i + 1], b[i][2], b[i][3]); }
                    if (i == 0) { mma16z(dv[0], pl[0], b[i][0], b[i][1]); mma16z(dv[1], pl[1], b[i][2], b[i][3]); }
                    if (i == 12) isc = __uint_as_float(lds32(sm + C_SCL));
                    if (i == 17) { l4 = l16; PIN(l4); l4 = (l4 >> 2) & 127; PIN(l4); }
                }
                SFENCE();
#pragma unroll
                for (int i = 0; i < 4; i++) u[i] = fmaf(d[2][i] + d[3][i], isc, (d[0][i] + d[1][i]) * isc);
                const uint32_t qs = sm + C_QM + warp * 256 + l4;
                sts32(qs, pack2(u[0], u[1])); sts32(qs + 128, pack2(u[2], u[3]));
                if (warp == 2) PROF(1);
                bar_sync(B_QK, 384);
                if (lds32(sm + C_BAD)) {
                    if (warp < nu) {
                        float e[2][4] = {{0, 0, 0, 0}, {0, 0, 0, 0}};
#pragma unroll 1
                        for (int k = 0; k < 12; k++) {
                            uint32_t ob[2]; lds64(ob, sm + C_OX + k * 256 + l4 * 2);
                            ldsm4t(pl[0], word + (k >> 1) * 14336 + (k & 1) * 1024); ldsm4t(pl[1], (word ^ 32) + (k >> 1) * 14336 + (k & 1) * 1024);
                            mma16(e[0], pl[0], ob[0], ob[1]); mma16(e[1], pl[1], ob[0], ob[1]);
                        }
                        float4* dst = (float4*)(g_slow + (((s & 1) * NH + head) * 20 + u0 + warp) * 256 + l4 * 2);
                        dst[0] = make_float4(e[0][0] * isc, e[0][1] * isc, e[0][2] * isc, e[0][3] * isc); dst[1] = make_float4(e[1][0] * isc, e[1][1] * isc, e[1][2] * isc, e[1][3] * isc);
                        __threadfence();
                    }
                    bar_arrive(B_RED, 384);
#pragma unroll
                    for (int i = 0; i < NP; i++) ldsm4t(pl[i], wvrd + i * 2048);
                    continue;
                }
                {
#pragma unroll
                    for (int f = NP + VPRE; f < NP + VPRE + VD; f++) ldsm4t(av[f], wvrd + f * 2048);
#pragma unroll
                    for (int f = NP; f < 20; f++) {
                        if (f >= NP + VPRE) SFENCE();
                        if (f >= NP + VPRE && f + VD < 20) ldsm4t(av[f + VD], wvrd + (f + VD) * 2048);
                        mma16(dv[f & 1], av[f], b[10 + (f >> 1)][2 * (f & 1)], b[10 + (f >> 1)][2 * (f & 1) + 1]);
                    }
                    sts128f(l16 + C_VP + warp * 512, (dv[0][0] + dv[1][0]) * isc, (dv[0][1] + dv[1][1]) * isc, (dv[0][2] + dv[1][2]) * isc, (dv[0][3] + dv[1][3]) * isc);
                    if (warp == 0) PROF(2);
                }
                if (warp >= nu || s + 1 == NSEG) {
                    bar_arrive(B_VP, 384);
                    if (s + 1 < NSEG) bar_arrive(B_RED, 384);
                    if (warp == 7) {
                        uint8_t* rec = rec0 + (size_t)s * (NH * REC) + j * R_J;
                        const uint64_t ef = policy_stream();
                        if (elect()) {
                            PROXY_FENCE();
                            bulk_s2g_ef(rec + R_Q, sm + C_QX, 4096, ef); bulk_s2g_ef(rec + R_K, sm + C_KX, 4096, ef); bulk_s2g_ef(rec + R_KM, sm + C_KM, 1024, ef);
                            BULK_COMMIT();
                            if (s + 3 < NSEG) {
                                const uint8_t* ln = g_acc + ((s + 3) >> 1) * 32768 + ((s + 3) & 1) * 128 + blk * 256;
                                asm volatile("prefetch.global.L2 [%0];" :: "l"(ln) : "memory");
                                if (blk < 4) asm volatile("prefetch.global.L2 [%0];" :: "l"(ln + 96 * 256) : "memory");
                            }
                            if (s + 2 < NSEG && blk < 10) asm volatile("cp.async.bulk.prefetch.L2.global [%0], 4096;" :: "l"(g_h + (s + 2) * SEG * DM + blk * 2048) : "memory");
                        }
                        __syncwarp();
                        bar_sync(B_VM, 160);
                        if (s + 1 < NSEG) {
                            if (elect()) { BULK_WAIT_READ(); h_fetch_b(mp, sm, s + 1); }
                            __syncwarp();
                            mbar_wait(sm + CB_OX, s & 1);
                        }
                        if (elect()) {
                            PROXY_FENCE();
                            bulk_s2g_ef(rec + R_VM, sm + C_VM, 1024, ef);
                            BULK_COMMIT();
                            if (s + 1 == NSEG) { BULK_WAIT(); bump(&g_flags.seg[s * 32 + head]); }
                        }
                        __syncwarp();
                    }
                    if (s + 1 == NSEG) break;
                    mbar_wait(sm + CB_XF, (s + 1) & 1);
                } else {
                    uint32_t w1 = word; PIN(w1); w1 ^= 32;
                    auto frag = [&](int f) { return ((f & 1) ? w1 : word) + (f >> 2) * 14336 + (f >> 1 & 1) * 1024; };
                    uint32_t a[24][4];
                    bar_arrive(B_VP, 384);
                    uint8_t* acc = g_acc + ((s + 1) >> 1) * 32768 + ((s + 1) & 1) * 128 + (u0 + warp) * 1280;
                    uint32_t ln = l16; PIN(ln); ln = ln >> 4 & 31;
                    uint32_t ox = sm + C_OX + ln * 8;
                    uint8_t* a4 = acc + (ln >> 3) * 256 + (ln & 7) * 16; uint8_t* a1 = acc + 1024 + ln * 4;
                    PIN(ox); PINL(a4); PINL(a1);
                    const bool tile = mbar_test(sm + CB_XF, (s + 1) & 1);
#pragma unroll
                    for (int f = 0; f < NW; f++) ldsm4t(a[f], frag(f));
                    float e[2][4];
                    uint32_t ob[12][2];
                    bar_sync(B_OWN, 128 + 32 * nu);
#pragma unroll
                    for (int k = 0; k < 4; k++) lds64(ob[k], ox + k * 256);
#pragma unroll
                    for (int k = 0; k < 4; k++) {
                        SFENCE();
                        if (k > 0) { ldsm4t(a[2 * k - 2 + NW], frag(2 * k - 2 + NW)); ldsm4t(a[2 * k - 1 + NW], frag(2 * k - 1 + NW)); }
                        if (k == 0) { mma16z(e[0], a[0], ob[0][0], ob[0][1]); mma16z(e[1], a[1], ob[0][0], ob[0][1]); }
                        else { mma16(e[0], a[2 * k], ob[k][0], ob[k][1]); mma16(e[1], a[2 * k + 1], ob[k][0], ob[k][1]); }
                    }
                    SFENCE();
                    ldsm4t(a[6 + NW], frag(6 + NW)); ldsm4t(a[7 + NW], frag(7 + NW));
                    PINL(xo); PINL(xt);
                    if (warp == 0) PROF(3);
                    mbar_wait(sm + CB_OX, s & 1);
#pragma unroll
                    for (int k = 4; k < 4 + OD; k++) lds64(ob[k], ox + k * 256);
                    if (warp == 1) PROF(4);
#pragma unroll
                    for (int k = 4; k < 12; k++) {
                        SFENCE();
                        if (k > 4 && k - 1 + OD < 12) lds64(ob[k - 1 + OD], ox + (k - 1 + OD) * 256);
                        if (k > 4 && 2 * k - 2 + NW < 24) { ldsm4t(a[2 * k - 2 + NW], frag(2 * k - 2 + NW)); ldsm4t(a[2 * k - 1 + NW], frag(2 * k - 1 + NW)); }
                        mma16(e[0], a[2 * k], ob[k][0], ob[k][1]); mma16(e[1], a[2 * k + 1], ob[k][0], ob[k][1]);
                    }
                    asm volatile("red.relaxed.gpu.global.add.noftz.v4.f16x2 [%0], {%1,%2,%3,%4};" :: "l"(a4), "r"(packh(e[0][0], e[0][1])), "r"(packh(e[0][2], e[0][3])),
                                 "r"(packh(e[1][0], e[1][1])), "r"(packh(e[1][2], 1.f)) : "memory");
                    asm volatile("red.relaxed.gpu.global.add.noftz.f16x2 [%0], %1;" :: "l"(a1), "r"(packh(e[1][3], 1.f)) : "memory");
                    bar_arrive(B_RED, 384);
                    if (warp == 0) { PROF(5); PROFG(25); }
                    if (!tile) mbar_wait(sm + CB_XF, (s + 1) & 1);
                }
            }
            float acc[16];
#pragma unroll
            for (int i = 0; i < 16; i++) acc[i] = 0.f;
            if (warp == 1) PROF(12);
            WG_FENCE();
#pragma unroll
            for (int n = 0; n < 40; n++) {
                const int i = n < 24 ? n : n < 32 ? n + 4 : n < 36 ? n - 8 : n, ks = pair_idx(i >> 1) * 2 + (i & 1);
                if (n == 32) mbar_wait(sm + CB_XG, (s + 1) & 1);
                wgmma_rs_n32(acc, wa[i], (pair_own(i >> 1) ? xo : xt) + (((ks >> 2) * 4096 + (ks & 3) * 32) >> 4));
                if (n % 4 == 2 && n / 4 < NP) { SFENCE(); ldsm4t(pl[n / 4], wvrd + n / 4 * 2048); }
            }
            WG_COMMIT();
            WG_WAIT(0);
            if (warp == 1) PROF(13);
            bar_sync(B_X, 256);
            uint32_t lx = l16; PIN(lx);
            const uint32_t dst = (lx ^ (lx >> 3 & 48)) + C_QX + wg * 20480 + w * 1024;
            sts128(dst, pack2(acc[0], acc[1]), pack2(acc[4], acc[5]), pack2(acc[8], acc[9]), pack2(acc[12], acc[13]));
            sts128(dst + 512, pack2(acc[2], acc[3]), pack2(acc[6], acc[7]), pack2(acc[10], acc[11]), pack2(acc[14], acc[15]));
            if (warp == 1) PROF(14);
            if (warp == 7 && s >= 0) { if (elect()) { BULK_WAIT(); bump(&g_flags.seg[s * 32 + head]); } __syncwarp(); }
            if (s < 0) {
                PPROF(6);
                mbar_wait(sm + CB_W2, 0);
                PPROF(7);
#pragma unroll
                for (int i = 0; i < NP; i++) ldsm4t(pl[i], wvrd + i * 2048);
            }
            s++;
        }
    } else {
        asm volatile("setmaxnreg.dec.sync.aligned.u32 56;");
        const uint32_t l16 = opaque(sm + lane * 16);
        if (w == 3) {
            const uint64_t ef = policy_stream();
            int c = 0;
#pragma unroll 1
            for (int d = 0; d < 21; d++) {
#pragma unroll 1
                for (; c < 21 && c - d < (d < ar.P[1] ? ar.P[0] : ar.P[2]); c++) {
                    if (c == 10) bar_sync(B_OWN, 160);
                    if (c == 15) bar_sync(B_VM, 160);
                    const uint32_t pb = sm + CB_PC + 8 * (c & 3);
                    if (elect()) {
                        mbar_expect(pb, c < 15 ? 16384 : 14336);
                        if (c < 10) tma2d_ef(sm + C_WV + c * 16384, c < 5 ? &mp.wq : &mp.wk, col0, c % 5 * 128, pb, ef);
                        else if (c < 15) tma2d(sm + C_WV + (c - 10) * 16384, &mp.wv, col0, (c - 10) * 128, pb);
                        else tma3d(sm + C_WO + (c - 15) * 14336, &mp.wo, head * DH + (c - 15 + 2 * j) % 6 * 32, u0, pb);
                    }
                    __syncwarp();
                }
                mbar_wait(sm + CB_PC + 8 * (d & 3), (d >> 2) & 1);
                if ((d == 4 || d == 9 || d == 20) && elect()) mbar_arrive(sm + (d == 4 ? CB_W : d == 9 ? CB_WK : CB_W2));
                __syncwarp();
            }
        } else if (w == 2) {
            if (elect()) {
                flag_add(&g_flags.h);
                PPROF2(12);
                flag_wait(&g_flags.h, 96);
                PPROF2(4);
                h_fetch_a(mp, sm, 0); h_fetch_b(mp, sm, 0);
                flags_release();
                flag_wait(&g_flags.v[head], 2);
                PPROF2(13);
                mbar_expect(sm + CB_VX, 4096);
                bulk_g2s(sm + C_VX, rec0 + j * 4096, 4096, sm + CB_VX);
            }
            __syncwarp();
            if (lane < 16 && blk < 80) g_modt[blk * 16 + lane] = 0;
        }
        uint32_t mx = 0;
#pragma unroll 1
        for (int i = 0; i < 5; i++) { uint32_t v[4]; lds128(v, l16 + C_MEM + (w * 5 + i) * 512); mx = absmax2(absmax2(absmax2(absmax2(mx, v[0]), v[1]), v[2]), v[3]); }
        sts32(sm + C_SCL, 0x3f800000u);
        int ex = 0;
        bool chk = false;
        int nslow = 0;
        uint32_t vb[2][4];
        { const uint32_t vxrd = l16 + lane * 112 + (((2 * w) ^ vswz(lane)) << 4); mbar_wait(sm + CB_VX, 0); ldsm4t(vb[0], vxrd + C_VX); ldsm4t(vb[1], (vxrd ^ 16) + C_VX); }
        bar_sync(B_MEM, 384);
        for (int s = 0; s < NSEG; s++) {
            uint32_t lq = l16; PIN(lq);
            const uint32_t l0 = lq >> 4 & 31, r0 = l0 & 7, m0 = l0 >> 3;
            uint32_t kb[2][4];
            const uint32_t kxrd = sm + C_KX + l0 * 64 + ((w ^ (r0 >> 1)) << 4);
            ldsm4t(kb[0], kxrd); ldsm4t(kb[1], kxrd + 2048);
            if (w == 0 && s + 1 < NSEG && elect()) {
                h_fetch_a(mp, sm, s + 1);
                mbar_expect(sm + CB_VX, 4096);
                bulk_g2s(sm + C_VX, rec0 + (size_t)(s + 1) * (NH * REC) + j * 4096, 4096, sm + CB_VX);
            }
            __syncwarp();
            const uint32_t r1 = (1 - 3 * (j >> 1)) << 24, r2 = (2 - 3 * ((j + 1) >> 1)) << 24;
            uint32_t qrd = sm + C_QM + ((m0 >> 1) + 2 * (m0 & 1)) * 128 + r0 * 16, scdst = sm + C_SC + j * 640 + w * 128 + ((l0 * 4) ^ (w * 32)),
                     sc1 = scdst + r1, sc2 = scdst + r2;
            PIN(qrd); PIN(scdst); PIN(sc1); PIN(sc2);
            for (;;) {
                sts32(sm + C_MAX + w * 4, __reduce_max_sync(0xffffffffu, max(mx & 0xffffu, mx >> 16)) >> 7);
                bar_sync(B_AUX, 128);
                uint32_t m4[4]; lds128(m4, sm + C_MAX);
                const int m = __shfl_sync(0xffffffffu, max(max(m4[0], m4[1]), max(m4[2], m4[3])), 0);
                const bool bad = chk && (m == 255 || m < 127 - 6 || ar.force);
                ex = min(max(ex + 130 - m, -40), 40);
                sts32(sm + C_BAD, bad);
                if (!bad) break;
                bar_sync(B_QK, 384);
                bar_sync(B_RED, 384);
                nslow++;
                if (w == 0 && elect()) {
                    asm volatile("red.release.gpu.global.add.u32 [%0], 1;" :: "l"(&g_flags.slow) : "memory");
                    for (int n = 0;; n++) {
                        uint32_t v; asm volatile("ld.acquire.gpu.global.u32 %0, [%1];" : "=r"(v) : "l"(&g_flags.slow) : "memory");
                        if (v >= 96u * nslow) break;
                        if (n > (1 << 23)) __trap();
                    }
                }
                bar_sync(B_AUX, 128);
                mx = 0;
#pragma unroll 1
                for (int i = 0; i < 10; i++) {
                    float4 a = make_float4(0, 0, 0, 0);
#pragma unroll 4
                    for (int h = 0; h < NH; h++) {
                        const float4 v = __ldcg((const float4*)(g_slow + ((((s & 1) * NH + h) * 20 + w * 5 + (i >> 1)) * 32 + l0) * 8) + (i & 1));
                        a.x += v.x; a.y += v.y; a.z += v.z; a.w += v.w;
                    }
                    const uint32_t o0 = pack2(a.x, a.y), o1 = pack2(a.z, a.w);
                    sts32(sm + C_MEM + (w * 10 + i) * 256 + l0 * 4, o0); sts32(sm + C_MEM + (w * 10 + i) * 256 + 128 + l0 * 4, o1);
                    mx = absmax2(absmax2(mx, o0), o1);
                }
                sts32(sm + C_SCL, 0x3f800000u);
                ex = 0; chk = false;
                bar_sync(B_MEM, 384);
            }
            if (s + 1 == NSEG) {
                bar_sync(B_QK, 384);
                bar_sync(B_VP, 384);
                const float4 y0 = lds128f(lq + C_VP + w * 512), y1 = lds128f(lq + C_VP + w * 512 + 2048);
                sts32(sm + C_VM + w * 256 + l0 * 4, pack2(y0.x + y1.x, y0.y + y1.y)); sts32(sm + C_VM + w * 256 + 128 + l0 * 4, pack2(y0.z + y1.z, y0.w + y1.w));
                bar_arrive(B_VM, 160);
                break;
            }
            if (w == 3) {
                uint32_t qa[2][4], km[2][4], x, y;
                bar_sync(B_QK, 384);
                ldsm4t(qa[0], qrd); ldsm4t(km[0], lq + C_KM); ldsm4t(qa[1], qrd + 512); ldsm4t(km[1], lq + C_KM + 512);
                SFENCE();
                score_tiles(qa, kb, km, x, y);
                stas1(sc1, x, sm + CB_SC + r1); stas1(sc2, x, sm + CB_SC + r2); stas1(sc1 + 128, y, sm + CB_SC + r1); stas1(sc2 + 128, y, sm + CB_SC + r2);
                sts32(scdst, x); sts32(scdst + 128, y);
            } else {
                uint32_t qa[2][4];
                bar_sync(B_QK, 384);
                ldsm4t(qa[0], qrd); ldsm4t(qa[1], qrd + 512);
                if (w == 0) PROF(6);
                const uint32_t x = score_tile(qa, kb);
                stas1(sc1, x, sm + CB_SC + r1); stas1(sc2, x, sm + CB_SC + r2);
                sts32(scdst, x);
            }
            __syncwarp();
            if (elect()) mbar_arrive(sm + CB_SC);
            SFENCE();
            if (w == 0) PROF(7);
            uint32_t scrd = sm + C_SC + (l0 & 3) * 128 + (((l0 >> 2) ^ (2 * (l0 & 3))) << 4), zrd = sm + C_SC + 512 + ((l0 * 4) ^ 96),
                     od = sm + C_OX + l0 * 8 + w * 256, od1 = od + r1 + 2048, od2 = od + r2 + 1024, vprd = lq + C_VP + w * 512, vmst = sm + C_VM + w * 256 + l0 * 4, ones = 0x3f803f80u, ones2 = 0x3f803f80u, zero = 0;
            PIN(scrd); PIN(zrd); PIN(od); PIN(od1); PIN(od2); PIN(vprd); PIN(vmst); PIN(ones); PIN(ones2); PIN(zero);
            mbar_wait(sm + CB_SC, s & 1);
            float sv[10];
            {
                uint32_t x[3][4], z[3];
#pragma unroll
                for (int p = 0; p < 3; p++) { lds128(x[p], scrd + p * 640); z[p] = lds32(zrd + p * 640); }
                if (w == 1) PROF(8);
#pragma unroll
                for (int i = 0; i < 4; i++) { sv[2 * i] = (lo_f(x[0][i]) + lo_f(x[1][i])) + lo_f(x[2][i]); sv[2 * i + 1] = (hi_f(x[0][i]) + hi_f(x[1][i])) + hi_f(x[2][i]); }
                sv[8] = (lo_f(z[0]) + lo_f(z[1])) + lo_f(z[2]); sv[9] = (hi_f(z[0]) + hi_f(z[1])) + hi_f(z[2]);
            }
            float mxs = fmaxf(fmaxf(fmaxf(sv[0], sv[1]), fmaxf(sv[2], sv[3])), fmaxf(fmaxf(fmaxf(sv[4], sv[5]), fmaxf(sv[6], sv[7])), fmaxf(sv[8], sv[9])));
            {
                const float a = __shfl_xor_sync(0xffffffffu, mxs, 1), b = __shfl_xor_sync(0xffffffffu, mxs, 2), c = __shfl_xor_sync(0xffffffffu, mxs, 3);
                mxs = fmaxf(fmaxf(mxs, a), fmaxf(b, c));
            }
#pragma unroll
            for (int i = 0; i < VPB; i++) sv[i] = ex2(sv[i] - mxs);
            SFENCE();
            bar_sync(B_VP, 384);
            const float4 y0 = lds128f(vprd), y1 = lds128f(vprd + 2048);
#pragma unroll
            for (int i = VPB; i < 10; i++) sv[i] = ex2(sv[i] - mxs);
            const uint32_t pa[4] = {pack2(sv[0], sv[1]), pack2(sv[4], sv[5]), pack2(sv[2], sv[3]), pack2(sv[6], sv[7])}, pm = pack2(sv[8], sv[9]);
            if (w == 2) PROF(9);
            {
                float o[2][4], o2[2][4], om[2][4], sx[4], sy[4];
                mma16z(sx, pa, ones, ones2);
                mma16z(o[0], pa, vb[0][0], vb[0][1]); mma16z(o2[0], pa, vb[0][2], vb[0][3]);
                mma8z(sy, pm, zero, ones);
                mma16z(o[1], pa, vb[1][0], vb[1][1]); mma16z(o2[1], pa, vb[1][2], vb[1][3]);
                SFENCE();
                const uint32_t vm0 = pack2(y0.x + y1.x, y0.y + y1.y), vm1 = pack2(y0.z + y1.z, y0.w + y1.w);
                mma8z(om[0], pm, zero, vm0); mma8z(om[1], pm, zero, vm1);
                float inv; asm("rcp.approx.ftz.f32 %0, %1;" : "=f"(inv) : "f"((sx[0] + sx[2]) + sy[0]));
                inv *= __int_as_float((127 + ex) << 23);
                const uint32_t a = pack2(((o[0][0] + o2[0][2]) + om[0][0]) * inv, ((o[0][1] + o2[0][3]) + om[0][1]) * inv),
                               b = pack2(((o[1][0] + o2[1][2]) + om[1][0]) * inv, ((o[1][1] + o2[1][3]) + om[1][1]) * inv);
                stas2(od1, a, b, sm + CB_OX + r1); stas2(od2, a, b, sm + CB_OX + r2);
                asm volatile("st.shared.v2.b32 [%0], {%1,%2};" :: "r"(od), "r"(a), "r"(b) : "memory");
                bar_arrive(B_OWN, 128 + 32 * nu);
                sts32(vmst, vm0); sts32(vmst + 128, vm1);
                bar_arrive(B_VM, 160);
                if (w == 0) PROF(10);
            }
            const uint8_t* acc = g_acc + ((s + 1) >> 1) * 32768 + ((s + 1) & 1) * 128 + w * 1280;
            const uint8_t* a4 = acc + (l0 >> 3) * 256 + (l0 & 7) * 16; const uint8_t* a1 = acc + 1024 + l0 * 4;
            PINL(a4); PINL(a1);
            const uint32_t* vf = &g_flags.v[(min(s + 2, NSEG - 1) >> 2) * 32 + head];
            uint32_t vok = 2;
            if (w == 0 && (s & 3) == 2) vok = ld_rlx(vf);
            if (w == 1 && elect()) { mbar_expect(sm + CB_SC, 1280); sts32(sm + C_SCL, (127 - ex) << 23); }
            __syncwarp();
            bar_sync(B_RED, 384);
            SFENCE();
            const uint32_t tw = clock();
            SFENCE();
            if (w == 1 && elect()) mbar_expect(sm + CB_OX, 2048);
            __syncwarp();
            { const uint32_t vxrd = lq + l0 * 112 + (((2 * w) ^ vswz(l0)) << 4); mbar_wait(sm + CB_VX, (s + 1) & 1); ldsm4t(vb[0], vxrd + C_VX); ldsm4t(vb[1], (vxrd ^ 16) + C_VX); }
            if (__any_sync(0xffffffffu, vok < 2)) flag_wait_warp(vf, 2);
            wait_until(tw + ar.D + (j == 2 ? ar.D2 : 0));
            if (w == 2) PROF(16);
            uint32_t v[5][4], z[5];
            int n = 0;
#pragma unroll
            for (int i = 0; i < 5; i++) {
                asm volatile("ld.relaxed.gpu.global.v4.u32 {%0,%1,%2,%3}, [%4];" : "=r"(v[i][0]), "=r"(v[i][1]), "=r"(v[i][2]), "=r"(v[i][3]) : "l"(a4 + (4 - i) * 5120) : "memory");
                asm volatile("ld.relaxed.gpu.global.u32 %0, [%1];" : "=r"(z[i]) : "l"(a1 + (4 - i) * 5120) : "memory");
            }
            while (__any_sync(0xffffffffu, min(min(min(v[0][3], z[0]), min(v[1][3], z[1])), min(min(min(v[2][3], z[2]), min(v[3][3], z[3])), min(v[4][3], z[4]))) < 0x50000000u)) {
#pragma unroll
                for (int i = 0; i < 5; i++) {
                    asm volatile("{ .reg .pred q; setp.lt.u32 q, %3, 0x50000000;\n@q ld.relaxed.gpu.global.v4.u32 {%0,%1,%2,%3}, [%4]; }" : "+r"(v[i][0]), "+r"(v[i][1]), "+r"(v[i][2]), "+r"(v[i][3]) : "l"(a4 + (4 - i) * 5120) : "memory");
                    asm volatile("{ .reg .pred q; setp.lt.u32 q, %0, 0x50000000;\n@q ld.relaxed.gpu.global.u32 %0, [%1]; }" : "+r"(z[i]) : "l"(a1 + (4 - i) * 5120) : "memory");
                }
                if (++n > SPIN_LIMIT) __trap();
            }
            if (w == 0) { PROF(11); PROFV(15, n); }
#pragma unroll
            for (int i = 0; i < 5; i++) {
                v[i][0] = h2b(v[i][0]); v[i][1] = h2b(v[i][1]); v[i][2] = h2b(v[i][2]); v[i][3] = h2b_lo(v[i][3], z[i]);
                stsm4(lq + C_MEM + w * 512 + (4 - i) * 2048, v[i][0], v[i][1], v[i][2], v[i][3]);
            }
            bar_sync(B_MEM, 384);
            SFENCE();
            mx = 0;
#pragma unroll
            for (int i = 0; i < 5; i++) mx = absmax2(absmax2(absmax2(absmax2(mx, v[i][0]), v[i][1]), v[i][2]), v[i][3]);
            chk = true;
        }
    }
}

struct SideMaps { CUtensorMap h, wv, ost, o, wo, slab3, slab2, ln[3], wgate, wup, wdown; };
constexpr int NRUN = 48;
struct Sched { uint16_t end[NRUN + 1]; uint8_t kind[NRUN + 1], block[NRUN + 1], lsplit[16], slab[16]; int bgrows; };
constexpr int SD_SL = REC / 3, SD_NSL = 12, SD_EPI = SD_NSL * SD_SL, SD_VEC = SD_EPI + 2 * 24576, SD_BAR = SD_VEC + 6400, SD_SMEM = SD_BAR + 768;
static_assert(SD_SMEM <= 232448, "side shared memory");

template <int NPC, bool V>
__device__ __forceinline__ void tile_out(const float (&acc)[8 * NPC], uint32_t eb, uint32_t efull, uint32_t eempty, int& eph, int w, int lane) {
    const int r = lane & 7, mi = lane >> 3, row = w * 16 + (mi & 1) * 8 + r;
    const uint32_t rb = V ? eb + (row >> 5) * 12288 + (row & 31) * 128 : eb + row * 128, sw = V ? vswz(row & 31) : r;
    mbar_wait(eempty, eph); eph ^= 1;
#pragma unroll
    for (int p = 0; p < NPC; p++) {
        const int oc = 2 * p + (mi >> 1);
        stsm4(rb + (oc >> 3) * (V ? 4096 : 8192) + (((oc & 7) ^ sw) << 4), pack2(acc[8 * p], acc[8 * p + 1]), pack2(acc[8 * p + 2], acc[8 * p + 3]),
              pack2(acc[8 * p + 4], acc[8 * p + 5]), pack2(acc[8 * p + 6], acc[8 * p + 7]));
    }
    PROXY_FENCE();
    __syncwarp();
    if (lane == 0) mbar_arrive(efull);
}

__device__ __forceinline__ uint32_t bmax(uint32_t a, uint32_t b) { uint32_t r; asm("max.bf16x2 %0, %1, %2;" : "=r"(r) : "r"(a), "r"(b)); return r; }
__device__ __forceinline__ void attn_units(uint32_t base, uint32_t dst, uint32_t bars, int mt, int lane) {
    const uint32_t FQ = bars, FV = bars + 8, EQ = bars + 16, PD = bars + 24, SE = bars + 32, EV = bars + 40, STOP = bars + 48;
    const int r = lane & 7, mi = lane >> 3, g = lane >> 2, t = lane & 3;
    const uint32_t tok = 8 * (r >> 1) + 2 * mi + (r & 1);
    const uint32_t qrd = opaque(base + R_Q + ((mi >> 1) * 8 + r) * 64 + (((2 * mt + (mi & 1)) ^ (r >> 1)) << 4)), mrd = opaque(base + lane * 16);
    uint32_t krd[4], vrd[8], ost[4], vis[2][4];
#pragma unroll
    for (int n = 0; n < 4; n++) {
        krd[n] = opaque(base + R_K + lane * 64 + ((n ^ (r >> 1)) << 4));
        ost[n] = opaque(dst + ((mi & 1) * 8 + r) * 128 + (((2 * n + (mi >> 1)) ^ r) << 4));
#pragma unroll
        for (int hf = 0; hf < 2; hf++) {
            const int lim = 8 * (g >> 1) + 2 * (2 * mt + hf) + (g & 1) - 8 * t - 2 * n;
            vis[hf][n] = opaque(lim < 0 ? 0u : lim < 1 ? 0xffffu : ~0u);
        }
    }
#pragma unroll
    for (int u = 0; u < 8; u++) vrd[u] = opaque(base + tok * 128 + ((u ^ vswz(tok)) << 4));
    const float scale = 0.07216878364870322f, l2e = 1.4426950408889634f;
#pragma unroll 1
    for (int ph = 0;; ph ^= 1) {
        mbar_wait(FQ, ph);
        float sc[5][4];
        uint32_t a[6][2][4], bb[6][5][4], bm[6][4];
        auto load = [&](int k2) {
            const uint32_t cb = (k2 >> 1) * R_J + (k2 & 1) * 2048;
            ldsm4t(a[k2][0], qrd + cb);
#pragma unroll
            for (int n = 0; n < 4; n++) ldsm4t(bb[k2][n], krd[n] + cb);
            ldsm4t(bb[k2][4], mrd + R_KM + (k2 >> 1) * R_J + (k2 & 1) * 512);
            ldsm4t(a[k2][1], qrd + cb + 1024);
        };
        const uint32_t stop = lds32(STOP);
        load(0); load(1);
        if (stop) break;
#pragma unroll
        for (int k2 = 0; k2 < 6; k2++) {
            SFENCE();
            if (k2 + 2 < 6) load(k2 + 2);
            else {
#pragma unroll
                for (int n = 0; n < 3; n++) { const int n4 = 3 * (k2 - 4) + n; ldsm4(bm[n4], mrd + R_VM + (n4 >> 1) * R_J + (n4 & 1) * 512); }
            }
#pragma unroll
            for (int n = 0; n < 5; n++) { if (k2 == 0) mma16z(sc[n], a[k2][0], bb[k2][n][0], bb[k2][n][1]); else mma16(sc[n], a[k2][0], bb[k2][n][0], bb[k2][n][1]); }
#pragma unroll
            for (int n = 0; n < 5; n++) mma16(sc[n], a[k2][1], bb[k2][n][2], bb[k2][n][3]);
        }
        if (lane == 0) mbar_arrive(EQ);
        uint32_t vb[6][4][4];
        auto vload = [&](int n4) {
#pragma unroll
            for (int u = 0; u < 4; u++) ldsm4t(vb[n4][u], vrd[(n4 & 1) * 4 + u] + (n4 >> 1) * 4096);
        };
        uint32_t sv[2][5], mx[2];
#pragma unroll
        for (int hf = 0; hf < 2; hf++) {
#pragma unroll
            for (int n = 0; n < 5; n++) {
                uint32_t u = pack2(sc[n][2 * hf], sc[n][2 * hf + 1]);
                u = pack2(lo_f(u) * scale, hi_f(u) * scale);
                sv[hf][n] = n < 4 ? (u & vis[hf][n & 3]) | (0xce6ece6eu & ~vis[hf][n & 3]) : u;
            }
            mx[hf] = bmax(bmax(bmax(sv[hf][0], sv[hf][1]), bmax(sv[hf][2], sv[hf][3])), sv[hf][4]);
        }
        uint32_t m2 = bmax(__byte_perm(mx[0], mx[1], 0x5410), __byte_perm(mx[0], mx[1], 0x7632));
        m2 = bmax(bmax(m2, __shfl_xor_sync(0xffffffffu, m2, 1)), bmax(__shfl_xor_sync(0xffffffffu, m2, 2), __shfl_xor_sync(0xffffffffu, m2, 3)));
        float v[2][10], sum[2];
#pragma unroll
        for (int hf = 0; hf < 2; hf++) {
            const float m = hf ? hi_f(m2) : lo_f(m2);
#pragma unroll
            for (int q = 0; q < 10; q++) asm("ex2.approx.ftz.f32 %0, %1;" : "=f"(v[hf][q]) : "f"(((q & 1 ? hi_f(sv[hf][q >> 1]) : lo_f(sv[hf][q >> 1])) - m) * l2e));
            sum[hf] = (((v[hf][0] + v[hf][1]) + (v[hf][2] + v[hf][3])) + ((v[hf][4] + v[hf][5]) + (v[hf][6] + v[hf][7]))) + (v[hf][8] + v[hf][9]);
        }
#pragma unroll
        for (int o = 1; o < 4; o <<= 1)
#pragma unroll
            for (int hf = 0; hf < 2; hf++) sum[hf] += __shfl_xor_sync(0xffffffffu, sum[hf], o);
        mbar_wait(FV, ph);
        vload(0); vload(1); vload(2); vload(3);
        SFENCE();
        uint32_t pa[2][4], pm[2];
#pragma unroll
        for (int hf = 0; hf < 2; hf++) {
            float inv; asm("rcp.approx.ftz.f32 %0, %1;" : "=f"(inv) : "f"(sum[hf]));
#pragma unroll
            for (int n = 0; n < 4; n++) pa[n >> 1][2 * (n & 1) + hf] = pack2(v[hf][2 * n] * inv, v[hf][2 * n + 1] * inv);
            pm[hf] = pack2(v[hf][8] * inv, v[hf][9] * inv);
        }
        mbar_wait(SE, ph ^ 1);
        float o[6][4][4];
#pragma unroll
        for (int n4 = 0; n4 < 7; n4++) {
            SFENCE();
            if (n4 == 1 || n4 == 2) vload(n4 + 3);
            if (n4 == 2 && lane == 0) mbar_arrive(EV);
            if (n4 < 6) {
#pragma unroll
                for (int u = 0; u < 4; u++) mma8z(o[n4][u], pm[0], pm[1], bm[n4][u]);
#pragma unroll
                for (int h = 0; h < 2; h++)
#pragma unroll
                    for (int u = 0; u < 4; u++) mma16(o[n4][u], pa[h], vb[n4][u][2 * h], vb[n4][u][2 * h + 1]);
            }
            if (n4 > 0) {
#pragma unroll
                for (int p = 0; p < 2; p++) {
                    const float (&x)[4] = o[n4 - 1][2 * p], (&y)[4] = o[n4 - 1][2 * p + 1];
                    stsm4(ost[((n4 - 1) & 1) * 2 + p] + ((n4 - 1) >> 1) * 4096, pack2(x[0], x[1]), pack2(x[2], x[3]), pack2(y[0], y[1]), pack2(y[2], y[3]));
                }
            }
        }
        __syncwarp();
        if (lane == 0) mbar_arrive(PD);
    }
}

__device__ __forceinline__ void ln2_row(const uint32_t (&av)[5][2], const uint2 (&xn)[5], int row, uint32_t vec, bf16* out, uint64_t ef, int lane) {
    uint32_t xv[10], hv[10];
#pragma unroll
    for (int q2 = 0; q2 < 5; q2++) {
        uint32_t ga[2]; lds64(ga, vec + q2 * 256);
        xv[2 * q2] = badd(xn[q2].x, bmul(ga[0], av[q2][0]));
        xv[2 * q2 + 1] = badd(xn[q2].y, bmul(ga[1], av[q2][1]));
    }
    ln_row(xv, hv);
    float r0 = 0, r1 = 0;
#pragma unroll
    for (int q2 = 0; q2 < 5; q2++) {
        const int c = row * DM + lane * 4 + q2 * 128;
        uint32_t sh[2], sc[2], gb[2], wv[2];
        lds64(sh, vec + 1280 + q2 * 256); lds64(sc, vec + 2560 + q2 * 256); lds64(gb, vec + 3840 + q2 * 256); lds64(wv, vec + 5120 + q2 * 256);
        const uint32_t h0 = badd(bmul(hv[2 * q2], badd(sc[0], 0x3f803f80u)), sh[0]), h1 = badd(bmul(hv[2 * q2 + 1], badd(sc[1], 0x3f803f80u)), sh[1]);
        r0 += lo_f(h0) * lo_f(wv[0]) + hi_f(h0) * hi_f(wv[0]); r1 += lo_f(h1) * lo_f(wv[1]) + hi_f(h1) * hi_f(wv[1]);
        st_ef(g_h2 + c, make_uint2(h0, h1), ef);
        st_ef(g_x1 + c, make_uint2(xv[2 * q2], xv[2 * q2 + 1]), ef);
        st_ef(out + c, make_uint2(badd(xv[2 * q2], bmul(gb[0], h0)), badd(xv[2 * q2 + 1], bmul(gb[1], h1))), ef);
    }
    const float rsum = warp_sum(r0 + r1);
    if (lane == 0) g_r[row] = __float2bfloat16_rn(rsum);
}
__device__ __forceinline__ int pos_row(int pos) { return (pos & ~31) + 8 * ((pos & 7) >> 1) + 2 * ((pos >> 3) & 3) + (pos & 1); }
__device__ __forceinline__ uint32_t claim(uint32_t* ctr) {
    uint32_t v; asm volatile("{ .reg .pred e; elect.sync _|e, -1; mov.u32 %0, 0; @e atom.relaxed.gpu.global.add.u32 %0, [%1], 1; }" : "=r"(v) : "l"(ctr) : "memory"); return v;
}
__device__ __forceinline__ void flag_wait_idle(const uint32_t* f, uint32_t target) {
    for (int n = 0; !__all_sync(0xffffffffu, ld_rlx(f) >= target); n++) { __nanosleep(400); if (n > (1 << 20)) __trap(); }
}
#define APROF(u)
__device__ __forceinline__ void attn_manager(const SideMaps& mp, uint32_t base, uint32_t stg, uint32_t bars, int& ph, const bf16* x, uint64_t ef) {
    const uint32_t FQ = bars, FV = bars + 8, EQ = bars + 16, PD = bars + 24, SE = bars + 32, EV = bars + 40, STOP = bars + 48;
    int prev = -1, pend = -1;
    auto flush = [&]() {
        if (pend >= 0 && elect()) { BULK_WAIT_READ(); mbar_arrive(SE); BULK_WAIT(); bump(&g_flags.at[(pend >> 7) * 32 + (pend & 31)]); APROF(pend); }
        pend = -1; __syncwarp();
    };
    auto store = [&]() {
        mbar_wait(PD, ph ^ 1);
        if (elect()) { PROXY_FENCE(); tma3d_store(&mp.ost, prev & ~31, (prev & 31) * 3, stg, ef, false); BULK_COMMIT(); }
        pend = prev; prev = -1;
    };
    int u = __reduce_max_sync(0xffffffffu, claim(&g_flags.anext));
    uint32_t fl = 0;
#pragma unroll 1
    for (;;) {
        if (u >= NSEG * NH || !__all_sync(0xffffffffu, fl >= 3)) {
            flush();
            if (u < NSEG * NH && __all_sync(0xffffffffu, ld_rlx(&g_flags.seg[u]) >= 3)) {}
            else {
                if (prev >= 0) { store(); flush(); }
                if (u >= NSEG * NH) break;
                flag_wait_warp(&g_flags.seg[u], 3);
            }
        }
        const uint8_t* rec = g_rec + (size_t)u * REC;
        const uint32_t nxt = claim(&g_flags.anext);
        mbar_wait(EQ, ph ^ 1);
        if (elect()) { mbar_expect(FQ, REC - R_Q); bulk_g2s_ef(base + R_Q, rec + R_Q, REC - R_Q, FQ, ef); }
        const int un = __reduce_max_sync(0xffffffffu, nxt);
        fl = ld_rlx(&g_flags.seg[min(un, NSEG * NH - 1)]);
        flush();
        mbar_wait(EV, ph ^ 1);
        if (elect()) {
            mbar_expect(FV, R_Q); bulk_g2s_ef(base, rec, R_Q, FV, ef);
            asm volatile("cp.async.bulk.prefetch.L2.global [%0], 1280;" :: "l"(x + u * DM) : "memory");
        }
        if (prev >= 0) store();
        prev = u; ph ^= 1; u = un;
    }
    if (elect()) { sts32(STOP, 1); mbar_arrive(FQ); }
    __syncwarp();
}

#define SPROF(tk, i)
#define FWAIT(bar, par) mbar_wait(bar, par)
#define EPROF()
#define TPROF(i)
__device__ __forceinline__ void side_tail(uint32_t wgu, uint32_t wgu_bar, int wgu_ph, uint32_t wd, uint32_t wd_bar, int wd_ph, uint32_t xb, uint32_t gbar, bf16* out, int tid) {
    const int warp = __shfl_sync(0xffffffffu, tid >> 5, 0), lane = tid & 31, r = lane & 7, mi = lane >> 3, blk = blockIdx.x;
    const uint32_t T_GU = xb, T_X = xb + 24576, T_RED = T_X + 10240, T_KEY = T_RED + 8192;
    TPROF(0);
    auto rkey = [](int idx) { uint32_t u = __ldcg((const unsigned short*)g_r + idx); u = (u & 0x8000u) ? (~u & 0xffffu) : (u | 0x8000u); return (u << 16) | (uint32_t)(S_TOK - 1 - idx); };
    {
        if (warp == 0 && lane < 15) flag_wait(&g_flags.ln[lane * 32], 128);
        bar_sync(1, 256);
        uint32_t k[8];
#pragma unroll
        for (int i = 0; i < 8; i++) { const int idx = warp * 240 + i * 32 + lane; k[i] = i * 32 + lane < 240 ? rkey(idx) : 0u; }
#pragma unroll 1
        for (int it = 0; it < 8; it++) {
            const uint32_t m = __reduce_max_sync(0xffffffffu, max(umax3(k[0], k[1], k[2]), max(umax3(k[3], k[4], k[5]), max(k[6], k[7]))));
#pragma unroll
            for (int i = 0; i < 8; i++) if (k[i] == m) k[i] = 0;
            if (lane == 0) sts32(T_KEY + (warp * 8 + it) * 4, m);
        }
    }
    bar_sync(1, 256);
    if (warp == 0) {
        uint32_t k[6];
        k[0] = lds32(T_KEY + lane * 4); k[1] = lds32(T_KEY + 128 + lane * 4);
        if (lane == 0) flag_wait(&g_flags.ln[15 * 32], 128);
        __syncwarp();
        TPROF(1);
#pragma unroll
        for (int i = 0; i < 4; i++) k[2 + i] = rkey(1920 + i * 32 + lane);
#pragma unroll 1
        for (int it = 0; it < 8; it++) {
            const uint32_t m = __reduce_max_sync(0xffffffffu, max(umax3(k[0], k[1], k[2]), umax3(k[3], k[4], k[5])));
#pragma unroll
            for (int i = 0; i < 6; i++) if (k[i] == m) k[i] = 0;
            if (lane == 0) sts32(T_KEY + 256 + it * 4, S_TOK - 1 - (m & 0xffffu));
        }
    }
    bar_sync(1, 256);
    TPROF(2);
    {
        const bf16* src = g_h2 + lds32(T_KEY + 256 + (tid & 7) * 4) * DM + (tid >> 3) * 8;
        uint4 v[3];
#pragma unroll
        for (int i = 0; i < 3; i++) if (i < 2 || tid < 128) v[i] = __ldcg((const uint4*)(src + i * 256));
#pragma unroll
        for (int i = 0; i < 3; i++) if (i < 2 || tid < 128) sts128(T_X + tid * 16 + i * 4096, v[i].x, v[i].y, v[i].z, v[i].w);
    }
    const int trow = lds32(T_KEY + 256 + (lane >> 2) * 4), tcol = (blk < 80 ? blk : 0) * 8 + (lane & 3) * 2;
    const uint32_t fx1 = __ldcg((const uint32_t*)(g_x1 + trow * DM + tcol)), fh2 = __ldcg((const uint32_t*)(g_h2 + trow * DM + tcol)),
                   fgb = __ldcg((const uint32_t*)(g_mod + 5 * DM + tcol));
    const float fr = __uint_as_float((uint32_t)__ldcg((const unsigned short*)g_r + trow) << 16);
    mbar_wait(wgu_bar, wgu_ph);
    bar_sync(1, 256);
    TPROF(3);
    {
        float dg[4] = {0, 0, 0, 0}, du[4] = {0, 0, 0, 0};
#pragma unroll
        for (int k = 0; k < 5; k++) {
            uint32_t b[4], ag[4], au[4];
            ldsm4(b, T_X + (warp * 5 + k) * 256 + (lane & 15) * 16);
            const uint32_t o = ((warp * 5 + k) * 16 + (mi >> 1) * 8 + r) * 32 + (mi & 1) * 16;
            ldsm4t(ag, wgu + o); ldsm4t(au, wgu + 20480 + o);
            mma16(dg, ag, b[0], b[1]); mma16(du, au, b[0], b[1]);
        }
        sts128f(T_RED + warp * 1024 + lane * 16, dg[0], dg[1], dg[2], dg[3]); sts128f(T_RED + warp * 1024 + 512 + lane * 16, du[0], du[1], du[2], du[3]);
    }
    bar_sync(1, 256);
    if (warp == 0) {
        float g4[4] = {0, 0, 0, 0}, u4[4] = {0, 0, 0, 0};
#pragma unroll
        for (int i = 0; i < 8; i++) {
            const float4 a = lds128f(T_RED + i * 1024 + lane * 16), b = lds128f(T_RED + i * 1024 + 512 + lane * 16);
            g4[0] += a.x; g4[1] += a.y; g4[2] += a.z; g4[3] += a.w; u4[0] += b.x; u4[1] += b.y; u4[2] += b.z; u4[3] += b.w;
        }
        float y[4];
#pragma unroll
        for (int i = 0; i < 4; i++) { const float gq = bfr(g4[i]); y[i] = bfr(__fdividef(gq, 1.f + __expf(-gq))) * bfr(u4[i]); }
        g_gu[blk * 64 + lane] = movm_t(pack2(y[0], y[1])); g_gu[blk * 64 + 32 + lane] = movm_t(pack2(y[2], y[3]));
        __syncwarp();
        TPROF(4);
        if (lane == 0) {
            flag_add(&g_flags.gu);
            if (blk < 80) {
                flag_wait(&g_flags.gu, 96);
                mbar_expect(gbar, 24576); bulk_g2s(T_GU, g_gu, 24576, gbar);
            }
        }
        __syncwarp();
    }
    if (blk < 80) {
        mbar_wait(wd_bar, wd_ph);
        mbar_wait(gbar, 0);
        TPROF(5);
        float d[2][4] = {{0, 0, 0, 0}, {0, 0, 0, 0}};
#pragma unroll
        for (int k2 = 0; k2 < 6; k2++) {
            uint32_t b[4]; ldsm4t(b, wd + (warp * 6 + k2) * 512 + lane * 16);
#pragma unroll
            for (int h = 0; h < 2; h++) {
                uint32_t a[4]; ldsm4(a, T_GU + ((warp * 12 + k2 * 2 + h) * 2 + (mi >> 1)) * 128 + r * 16);
                mma16(d[h], a, b[2 * h], b[2 * h + 1]);
            }
        }
        asm volatile("st.shared.v2.f32 [%0], {%1,%2};" :: "r"(T_X + warp * 256 + lane * 8), "f"(d[0][0] + d[1][0]), "f"(d[0][1] + d[1][1]) : "memory");
        bar_sync(1, 256);
        if (warp == 0) {
            float y0 = 0, y1 = 0;
#pragma unroll
            for (int i = 0; i < 8; i++) { const float2 a = lds64f(T_X + i * 256 + lane * 8); y0 += a.x; y1 += a.y; }
            const float sg = bfr(__fdividef(1.f, 1.f + __expf(-fr)));
            const float b0 = bfr(lo_f(fh2) + bfr(bfr(y0) * sg)), b1 = bfr(hi_f(fh2) + bfr(bfr(y1) * sg));
            *(uint32_t*)(out + trow * DM + tcol) = pack2(lo_f(fx1) + bfr(lo_f(fgb) * b0), hi_f(fx1) + bfr(hi_f(fgb) * b1));
        }
    }
    TPROF(6);
}

__global__ void __launch_bounds__(512, 1) k_side(const __grid_constant__ SideMaps mp, const __grid_constant__ Sched sd, const bf16* __restrict__ x,
                                                 const bf16* __restrict__ wr, const bf16* __restrict__ cin, const bf16* __restrict__ wmod, bf16* __restrict__ out) {
    extern __shared__ __align__(1024) uint8_t smraw[];
    const uint32_t sm = smem_u32(smraw);
    if (sm & 1023) __trap();
    const uint32_t FULL = sm + SD_BAR, EMPTY = FULL + 96, EFULL = FULL + 192, EEMPTY = EFULL + 16, IFULL = EFULL + 32, IEMPTY = EFULL + 64, IQ = EFULL + 96,
                   VEC = EFULL + 112, GBAR = EFULL + 120, LNDONE = EFULL + 128, LNFREE = EFULL + 136, GO = EFULL + 144, ATT = FULL + 512;
    const int tid = threadIdx.x, warp = __shfl_sync(0xffffffffu, tid >> 5, 0), lane = tid & 31;
    const uint64_t ef = policy_stream();
    if (tid >= 32 && tid < 32 + SD_NSL) { mbar_init(FULL + 8 * (tid - 32), 1); mbar_init(EMPTY + 8 * (tid - 32), 8); asm volatile("fence.mbarrier_init.release.cluster;" ::: "memory"); }
    if (tid >= 64 && tid < 96) {
        const int k = tid & 7;
        if (k < 6) mbar_init(ATT + (tid - 64) * 8, k == 2 || k == 3 || k == 5 ? 2 : 1); else sts32(ATT + (tid - 64) * 8, 0);
        asm volatile("fence.mbarrier_init.release.cluster;" ::: "memory");
    }
    if (tid == 0) {
        mbar_init(GO, 1);
        for (int i = 0; i < 2; i++) { mbar_init(EFULL + 8 * i, 4); mbar_init(EEMPTY + 8 * i, 1); }
        for (int i = 0; i < 4; i++) { mbar_init(IFULL + 8 * i, 1); mbar_init(IEMPTY + 8 * i, 11); }
        mbar_init(VEC, 1); mbar_init(GBAR, 1); mbar_init(LNDONE, 8); mbar_init(LNFREE, 1);
        asm volatile("fence.mbarrier_init.release.cluster;" ::: "memory");
    }
    __syncthreads();
    if (warp >= 12) {
        asm volatile("setmaxnreg.dec.sync.aligned.u32 72;");
        mbar_wait(GO, 0);
        bool vec = false;
#pragma unroll 1
        for (;;) {
            const int t = __reduce_max_sync(0xffffffffu, claim(&g_flags.bnext));
            if (t < 40) {
                flag_wait_idle(&g_flags.v[0], 2);
                float a0 = 0, a1 = 0;
                const uint32_t* src = (const uint32_t*)(wmod + 2 * DM + t * 64) + lane;
#pragma unroll 1
                for (int k0 = 0; k0 < DM; k0 += 64) {
                    const uint32_t cv = silu2(__ldg((const uint32_t*)cin + k0 / 2 + lane));
#pragma unroll 1
                    for (int k1 = 0; k1 < 64; k1 += 32) {
                        uint32_t wv[32];
#pragma unroll
                        for (int k = 0; k < 32; k++) wv[k] = __ldcs(src + (size_t)(k0 + k1 + k) * (3 * DM));
#pragma unroll
                        for (int k = 0; k < 32; k += 2) {
                            const uint32_t c2 = __shfl_sync(0xffffffffu, cv, (k1 + k) >> 1);
                            a0 += lo_f(c2) * lo_f(wv[k]) + hi_f(c2) * lo_f(wv[k + 1]); a1 += lo_f(c2) * hi_f(wv[k]) + hi_f(c2) * hi_f(wv[k + 1]);
                        }
                    }
                }
                ((uint32_t*)(g_mod + 2 * DM + t * 64))[lane] = pack2(a0, a1);
                __syncwarp();
                if (lane == 0) flag_add(&g_flags.mod);
                continue;
            }
            if (!vec) {
                vec = true;
                if (warp == 12) {
                    flag_wait_idle(&g_flags.mod, 40);
                    if (elect()) { mbar_expect(VEC, 6400); bulk_g2s(sm + SD_VEC, g_mod + 2 * DM, 5120, VEC); bulk_g2s(sm + SD_VEC + 5120, wr, 1280, VEC); }
                    __syncwarp();
                    mbar_wait(VEC, 0);
                }
            }
            const int pos = t - 40, b = pos >> 7;
            if (pos >= sd.bgrows) break;
            const int ls = sd.lsplit[b], row = pos_row(pos);
            flag_wait_idle(&g_flags.o[b * 32], 4u << ls);
            float av[20];
#pragma unroll
            for (int n = 0; n < 20; n++) av[n] = 0.f;
            const bf16* sl = g_slab + ((size_t)sd.slab[b] * 128 + (pos & 127)) * DM + lane * 4;
#pragma unroll 1
            for (int k = 0; k < (1 << ls); k += 2) {
                uint2 z[2][5];
#pragma unroll
                for (int n = 0; n < 10; n++) z[n / 5][n % 5] = ld_ef(sl + (size_t)(k + n / 5) * (128 * DM) + n % 5 * 128, ef);
#pragma unroll
                for (int n = 0; n < 10; n++) { const uint2 v = z[n / 5][n % 5]; float* a = av + 4 * (n % 5); a[0] += lo_f(v.x); a[1] += hi_f(v.x); a[2] += lo_f(v.y); a[3] += hi_f(v.y); }
            }
            uint2 xn[5];
#pragma unroll
            for (int q2 = 0; q2 < 5; q2++) xn[q2] = ld_ef(x + row * DM + lane * 4 + q2 * 128, ef);
            uint32_t ap[5][2];
#pragma unroll
            for (int n = 0; n < 10; n++) ap[n >> 1][n & 1] = pack2(av[2 * n], av[2 * n + 1]);
            mbar_wait(VEC, 0);
            ln2_row(ap, xn, row, sm + SD_VEC + lane * 8, out, ef, lane);
            __syncwarp();
            if (lane == 0) flag_add(&g_flags.ln[b * 32]);
        }
    } else if (warp >= 8) {
      asm volatile("setmaxnreg.dec.sync.aligned.u32 40;");
      int aph = 0; bool att = false;
      auto manage = [&]() {
          bar_sync(2, 384);
          attn_manager(mp, sm + (warp - 8) * REC, sm + SD_EPI + (warp - 8) * 12288, ATT + (warp - 8) * 64, aph, x, ef);
          bar_sync(2, 384);
      };
      if (warp == 8) {
        uint32_t nxt = claim(&g_flags.next);
        int st = 0, ph = 1, run = 0;
        auto take = [&](int n, int bytes) {
            mbar_wait(EMPTY + 8 * (st + n - 1), ph);
            asm volatile("{ .reg .pred p; setp.lt.u32 p, %2, %3; @p mbarrier.arrive.expect_tx.shared::cta.b64 _, [%0], %1; }"
                :: "r"(FULL + 8 * (st + lane)), "r"(lane ? 0 : bytes), "r"(lane), "r"(n) : "memory");
        };
        auto step = [&](int n) { st += n; if (st == SD_NSL) { st = 0; ph ^= 1; } };
#pragma unroll 1
        for (int q = 0;; q++) {
            const int tk = __reduce_max_sync(0xffffffffu, nxt);
            while (tk >= sd.end[run]) run++;
            const int kind = sd.kind[run], b = sd.block[run], i = tk - (run ? sd.end[run - 1] : 0), ls = sd.lsplit[b];
            mbar_wait(IEMPTY + 8 * (q & 3), ((q >> 2) & 1) ^ 1);
            if (elect()) {
                sts32(IQ + 4 * (q & 3), kind << 12 | b << 8 | (i & 255));
                mbar_arrive(IFULL + 8 * (q & 3));
            }
            __syncwarp();
            const int pad = kind == 2 ? st & 1 : (12 - st) % 3;
            if (pad) { take(pad, 0); step(pad); }
            int kb0 = 0;
            if (q == 0) {
                if (kind == 0) {
#pragma unroll 1
                    for (; kb0 < 4; kb0++) { take(3, 40960); if (elect()) tma3d(sm + st * SD_SL + 16384, &mp.wv, kb0 * 64, i * 3, FULL + 8 * st); step(3); }
                }
                flag_wait_warp(&g_flags.h, 96);
                if (elect()) mbar_arrive(GO);
#pragma unroll 1
                for (int kb = 0; kb < kb0; kb++) if (elect()) tma2d(sm + kb * 3 * SD_SL, &mp.h, kb * 64, b * 128, FULL + 24 * kb);
            }
            if (kind == 0) {
#pragma unroll 1
                for (int kb = kb0; kb < 10; kb++) {
                    take(3, 40960);
                    if (elect()) { tma2d(sm + st * SD_SL, &mp.h, kb * 64, b * 128, FULL + 8 * st); tma3d(sm + st * SD_SL + 16384, &mp.wv, kb * 64, i * 3, FULL + 8 * st); }
                    if (kb == 8) nxt = claim(&g_flags.next);
                    step(3);
                }
            } else if (kind == 1) {
                if (!att) manage();
                att = true;
                nxt = claim(&g_flags.next);
            } else if (kind == 2) {
                const int nst = 192 >> ls, kf = (i >> 1) * nst * 32;
                const uint32_t* af = &g_flags.at[b * 32 + (i >> 1) * (32 >> ls) + (lane & ((32 >> ls) - 1))];
                int kb = 0;
                if (!__all_sync(0xffffffffu, ld_rlx(af) >= 4)) {
#pragma unroll 1
                    for (; kb < 6; kb++) { take(2, 28672); if (elect()) tma3d(sm + st * SD_SL + 8192, &mp.wo, kf + kb * 32, (i & 1) * 5, FULL + 8 * st); step(2); }
                    flag_wait_warp(af, 4);
#pragma unroll 1
                    for (int n = 0; n < 6; n++) { const int sl = (st + 2 * n) % SD_NSL; if (elect()) tma2d(sm + sl * SD_SL, &mp.o, kf + n * 32, b * 128, FULL + 8 * sl); }
                    if (nst == 6) nxt = claim(&g_flags.next);
                }
#pragma unroll 1
                for (; kb < nst; kb++) {
                    take(2, 28672);
                    if (elect()) { tma3d(sm + st * SD_SL + 8192, &mp.wo, kf + kb * 32, (i & 1) * 5, FULL + 8 * st); tma2d(sm + st * SD_SL, &mp.o, kf + kb * 32, b * 128, FULL + 8 * st); }
                    if (kb == nst - 2) nxt = claim(&g_flags.next);
                    step(2);
                }
            } else if (kind == 3) {
                take(3, 40960);
                flag_wait_warp(&g_flags.o[b * 32], 4u << ls);
                if (elect())
                    asm volatile("cp.async.bulk.tensor.4d.shared::cluster.global.mbarrier::complete_tx::bytes.L2::cache_hint [%0], [%1, {0, 0, %3, %4}], [%2], %5;"
                        :: "r"(sm + st * SD_SL), "l"((uint64_t)&mp.ln[ls - 3]), "r"(FULL + 8 * st), "r"(i * (32 >> ls)), "r"((int)sd.slab[b]), "l"(ef) : "memory");
                step(3);
                mbar_wait(IEMPTY + 8 * (q & 3), (q >> 2) & 1);
                nxt = claim(&g_flags.next);
            } else {
                if (blockIdx.x < 96) {
                    take(3, 40960);
                    if (elect()) {
#pragma unroll 1
                        for (int c = 0; c < 5; c++) { tma2d(sm + st * SD_SL + c * 4096, &mp.wgate, blockIdx.x * 16, c * 128, FULL + 8 * st); tma2d(sm + st * SD_SL + 20480 + c * 4096, &mp.wup, blockIdx.x * 16, c * 128, FULL + 8 * st); }
                    }
                    step(3);
                }
                if (blockIdx.x < 80) {
                    take(3, 24576);
                    if (elect()) {
#pragma unroll 1
                        for (int c = 0; c < 6; c++) tma2d(sm + st * SD_SL + c * 4096, &mp.wdown, blockIdx.x * 8, c * 256, FULL + 8 * st);
                    }
                }
                if (elect()) flags_release();
                break;
            }
        }
      } else {
        const int wg = warp - 9; int ph = 0;
#pragma unroll 1
        for (int q = 0;; q++) {
            mbar_wait(IFULL + 8 * (q & 3), (q >> 2) & 1);
            const int it = __shfl_sync(0xffffffffu, lds32(IQ + 4 * (q & 3)), 0);
            if (elect()) mbar_arrive(IEMPTY + 8 * (q & 3));
            const int kind = (it >> 12) & 7, b = (it >> 8) & 15, i = it & 255;
            if (kind == 4) break;
            if (kind == 1) { if (!att) manage(); att = true; continue; }
            if ((wg == 2) != (kind == 3)) continue;
            if (kind == 3) {
                mbar_wait(LNDONE, ph); ph ^= 1;
                if (elect()) { mbar_arrive(LNFREE); flag_add(&g_flags.ln[b * 32], 32 >> sd.lsplit[b]); }
            } else {
#pragma unroll 1
                for (int rd = 0; rd < (kind == 2 ? 2 : 1); rd++) {
                    mbar_wait(EFULL + 8 * wg, ph); ph ^= 1;
                    const uint32_t src = sm + SD_EPI + wg * 24576;
                    if (elect()) {
                        if (kind == 2) tma3d_store(rd ? &mp.slab2 : &mp.slab3, (sd.slab[b] + (i >> 1)) * 128 + wg * 64, (i & 1) * 5 + rd * 3, src, ef, false);
                        else {
                            uint8_t* dst = g_rec + (size_t)((b * 4 + wg * 2) * NH + i) * REC;
                            bulk_s2g_ef(dst, src, 12288, ef); bulk_s2g_ef(dst + NH * REC, src + 12288, 12288, ef);
                        }
                        BULK_COMMIT();
                        BULK_WAIT_READ();
                        mbar_arrive(EEMPTY + 8 * wg);
                    }
                    __syncwarp();
                }
                if (elect()) { BULK_WAIT(); bump(kind == 0 ? &g_flags.v[b * 32 + i] : &g_flags.o[b * 32]); }
            }
            __syncwarp();
        }
      }
    } else {
        asm volatile("setmaxnreg.inc.sync.aligned.u32 200;");
        const int wg = warp >> 2, w = warp & 3;
        int st = 0, ph = 0, eph = 1, lph = 1;
        bool att = false;
        const uint32_t eb = sm + SD_EPI + wg * 24576;
        for (int q = 0;; q++) {
            mbar_wait(IFULL + 8 * (q & 3), (q >> 2) & 1);
            const int itc = __shfl_sync(0xffffffffu, lds32(IQ + 4 * (q & 3)), 0);
            if (lane == 0) mbar_arrive(IEMPTY + 8 * (q & 3));
            const int kind = (itc >> 12) & 7, b = (itc >> 8) & 15, i = itc & 255;
            const int ns = kind == 2 ? 2 : 3, pad = kind == 2 ? st & 1 : (12 - st) % 3;
            if (pad) {
                mbar_wait(FULL + 8 * st, ph);
                if (lane < pad) mbar_arrive(EMPTY + 8 * (st + lane));
                st += pad; if (st == SD_NSL) { st = 0; ph ^= 1; }
            }
            const uint32_t rel = EMPTY + 8 * lane;
            if (kind == 0) {
                float acc[96];
#pragma unroll
                for (int n = 0; n < 96; n++) acc[n] = 0.f;
                int prev = -1;
                for (int kb = 0; kb < 10; kb++) {
                    FWAIT(FULL + 8 * st, ph);
                    const uint32_t base = sm + st * SD_SL;
                    WG_FENCE();
#pragma unroll
                    for (int ks = 0; ks < 4; ks++)
                        wgmma_ss_n192_tb(acc, mkdesc(base + wg * 8192 + ks * 32, 16, 1024), mkdesc(base + 16384 + ks * 2048, 8192, 1024), (kb | ks) != 0);
                    WG_COMMIT();
                    if (prev >= 0) { WG_WAIT(1); if (lane < ns) mbar_arrive(rel + 8 * prev); }
                    prev = st;
                    st += ns; if (st == SD_NSL) { st = 0; ph ^= 1; }
                }
                WG_WAIT(0);
                if (lane < ns) mbar_arrive(rel + 8 * prev);
                EPROF();
                tile_out<12, true>(acc, eb, EFULL + 8 * wg, EEMPTY + 8 * wg, eph, w, lane);
            } else if (kind == 1) {
                if (!att) {
                    bar_sync(2, 384);
                    attn_units(sm + (warp >> 1) * REC, sm + SD_EPI + (warp >> 1) * 12288 + (warp & 1) * 2048, ATT + (warp >> 1) * 64, warp & 1, lane);
                    bar_sync(2, 384);
                }
                att = true;
            } else if (kind == 2) {
                float acc[96], acc2[64];
#pragma unroll
                for (int n = 0; n < 96; n++) acc[n] = 0.f;
#pragma unroll
                for (int n = 0; n < 64; n++) acc2[n] = 0.f;
                int prev = -1;
                for (int kb = 192 >> sd.lsplit[b]; kb > 0; kb--) {
                    const uint32_t base = sm + st * SD_SL;
                    FWAIT(FULL + 8 * st, ph);
                    WG_FENCE();
#pragma unroll
                    for (int ks = 0; ks < 2; ks++) {
                        const uint64_t da = (mkdesc(base + wg * 4096 + ks * 32, 16, 512) & ~(3ull << 62)) | (2ull << 62);
                        wgmma_ss_n192_tb(acc, da, mkdesc(base + 8192 + ks * 2048, 4096, 1024), 1);
                        wgmma_ss_n128_tb(acc2, da, mkdesc(base + 8192 + 3 * 4096 + ks * 2048, 4096, 1024), 1);
                    }
                    WG_COMMIT();
                    if (prev >= 0) { WG_WAIT(1); if (lane < ns) mbar_arrive(rel + 8 * prev); }
                    prev = st;
                    st += ns; if (st == SD_NSL) { st = 0; ph ^= 1; }
                }
                WG_WAIT(0);
                if (lane < ns) mbar_arrive(rel + 8 * prev);
                EPROF();
                tile_out<12, false>(acc, eb, EFULL + 8 * wg, EEMPTY + 8 * wg, eph, w, lane);
                tile_out<8, false>(acc2, eb, EFULL + 8 * wg, EEMPTY + 8 * wg, eph, w, lane);
            } else if (kind == 3) {
                const int ls = sd.lsplit[b], rs = 5 - ls, row = pos_row(b * 128 + (i << rs) + (warp & ((1 << rs) - 1)));
                uint2 xn[5];
#pragma unroll
                for (int q2 = 0; q2 < 5; q2++) xn[q2] = ld_ef(x + row * DM + lane * 4 + q2 * 128, ef);
                mbar_wait(VEC, 0);
                FWAIT(FULL + 8 * st, ph);
                const uint32_t base = sm + st * SD_SL;
#pragma unroll 1
                for (int c = tid; c < (320 << rs); c += 256) {
                    float a0 = 0, a1 = 0;
#pragma unroll 1
                    for (int k = 0; k < (1 << ls); k += 8) {
                        uint32_t z[8];
#pragma unroll
                        for (int u = 0; u < 8; u++) z[u] = lds32(base + c * 4 + ((k + u) * 1280 << rs));
#pragma unroll
                        for (int u = 0; u < 8; u++) { a0 += lo_f(z[u]); a1 += hi_f(z[u]); }
                    }
                    sts32(base + c * 4, pack2(a0, a1));
                }
                bar_sync(1, 256);
                uint32_t av[5][2];
#pragma unroll
                for (int q2 = 0; q2 < 5; q2++) lds64(av[q2], base + (warp & ((1 << rs) - 1)) * 1280 + lane * 8 + q2 * 256);
                PROXY_FENCE();
                __syncwarp();
                if (lane < 3) mbar_arrive(rel + 8 * st);
                st += 3; if (st == SD_NSL) { st = 0; ph ^= 1; }
                if (warp < (1 << rs)) ln2_row(av, xn, row, sm + SD_VEC + lane * 8, out, ef, lane);
                __syncwarp();
                mbar_wait(LNFREE, lph); lph ^= 1;
                if (lane == 0) mbar_arrive(LNDONE);
            } else {
                if (blockIdx.x < 96) {
                    mbar_wait(EEMPTY + 8 * wg, eph);
                    int s1 = st + 3, p1 = ph; if (s1 == SD_NSL) { s1 = 0; p1 ^= 1; }
                    side_tail(sm + st * SD_SL, FULL + 8 * st, ph, sm + s1 * SD_SL, FULL + 8 * s1, p1, sm + SD_EPI, GBAR, out, tid);
                }
                break;
            }
        }
    }
    __syncwarp();
    asm volatile("griddepcontrol.wait;" ::: "memory");
}

typedef CUresult (*EncodeFn)(CUtensorMap*, CUtensorMapDataType, cuuint32_t, void*, const cuuint64_t*, const cuuint64_t*, const cuuint32_t*, const cuuint32_t*,
                             CUtensorMapInterleave, CUtensorMapSwizzle, CUtensorMapL2promotion, CUtensorMapFloatOOBfill);
static EncodeFn s_encode = nullptr;
static void make_map(CUtensorMap* m, const void* p, int rows, int cols, int box_rows, int box_cols = 64) {
    cuuint64_t dims[2] = {(cuuint64_t)cols, (cuuint64_t)rows}, strides[1] = {(cuuint64_t)cols * 2};
    cuuint32_t box[2] = {(cuuint32_t)box_cols, (cuuint32_t)box_rows}, es[2] = {1, 1};
    s_encode(m, CU_TENSOR_MAP_DATA_TYPE_BFLOAT16, 2, (void*)p, dims, strides, box, es, CU_TENSOR_MAP_INTERLEAVE_NONE,
             box_cols == 64 ? CU_TENSOR_MAP_SWIZZLE_128B : box_cols == 32 ? CU_TENSOR_MAP_SWIZZLE_64B : CU_TENSOR_MAP_SWIZZLE_NONE, CU_TENSOR_MAP_L2_PROMOTION_L2_256B, CU_TENSOR_MAP_FLOAT_OOB_FILL_NONE);
}
static void make_map3(CUtensorMap* m, const void* p, int rows, int cols, int box_rows, int box_chunks, int cw = 64) {
    cuuint64_t dims[3] = {(cuuint64_t)cw, (cuuint64_t)rows, (cuuint64_t)cols / cw}, strides[2] = {(cuuint64_t)cols * 2, (cuuint64_t)cw * 2};
    cuuint32_t box[3] = {(cuuint32_t)cw, (cuuint32_t)box_rows, (cuuint32_t)box_chunks}, es[3] = {1, 1, 1};
    s_encode(m, CU_TENSOR_MAP_DATA_TYPE_BFLOAT16, 3, (void*)p, dims, strides, box, es, CU_TENSOR_MAP_INTERLEAVE_NONE,
             cw == 64 ? CU_TENSOR_MAP_SWIZZLE_128B : CU_TENSOR_MAP_SWIZZLE_64B, CU_TENSOR_MAP_L2_PROMOTION_L2_256B, CU_TENSOR_MAP_FLOAT_OOB_FILL_NONE);
}
template <typename T> static void* sym(T& s) { void* p = nullptr; cudaGetSymbolAddress(&p, s); return p; }

static void make_map_ln(CUtensorMap* m, const void* p, int ls) {
    cuuint64_t dims[4] = {128, 5, 128, NSLAB}, strides[3] = {256, DM * 2, 128 * DM * 2};
    cuuint32_t box[4] = {128, 5, (cuuint32_t)(32 >> ls), (cuuint32_t)(1 << ls)}, es[4] = {1, 1, 1, 1};
    s_encode(m, CU_TENSOR_MAP_DATA_TYPE_BFLOAT16, 4, (void*)p, dims, strides, box, es, CU_TENSOR_MAP_INTERLEAVE_NONE,
             CU_TENSOR_MAP_SWIZZLE_NONE, CU_TENSOR_MAP_L2_PROMOTION_L2_256B, CU_TENSOR_MAP_FLOAT_OOB_FILL_NONE);
}
static void make_sched(Sched* sd, const char* order, const char* lsplit) {
    int slab = 0, end = 0, r = 0;
    for (int b = 0; b < 16; b++) { sd->lsplit[b] = lsplit[b] - '0'; sd->slab[b] = slab; slab += 1 << sd->lsplit[b]; }
    sd->bgrows = S_TOK;
    for (; r < NRUN && order[2 * r]; r++) {
        const char k = order[2 * r], c = order[2 * r + 1]; const int b = c <= '9' ? c - '0' : c - 'a' + 10;
        sd->kind[r] = k == 'V' ? 0 : k == 'T' ? 1 : k == 'O' ? 2 : 3; sd->block[r] = b;
        end += k == 'O' ? 2 << sd->lsplit[b] : k == 'L' ? 4 << sd->lsplit[b] : k == 'T' ? b : 32;
        sd->end[r] = end;
        if (k == 'L') sd->bgrows -= 128;
    }
    for (; r <= NRUN; r++) { sd->end[r] = 65535; sd->kind[r] = 4; sd->block[r] = 0; }
}

extern "C" void kernel_launch(void* const* d_in, const int* in_sizes, int n_in, void* d_out, int out_size) {
    const bf16 *x = (const bf16*)d_in[0], *mem0 = (const bf16*)d_in[1], *Wq = (const bf16*)d_in[2], *Wk = (const bf16*)d_in[3],
               *Wv = (const bf16*)d_in[4], *Wo = (const bf16*)d_in[5], *wr = (const bf16*)d_in[8], *wgate = (const bf16*)d_in[9],
               *wup = (const bf16*)d_in[10], *wdown = (const bf16*)d_in[11], *c = (const bf16*)d_in[12], *wmod = (const bf16*)d_in[13];
    bf16* out = (bf16*)d_out;
    if (!s_encode) {
        cudaDriverEntryPointQueryResult qr;
        cudaGetDriverEntryPoint("cuTensorMapEncodeTiled", (void**)&s_encode, cudaEnableDefault, &qr);
        cudaFuncSetAttribute(k_side, cudaFuncAttributeMaxDynamicSharedMemorySize, SD_SMEM);
        cudaFuncSetAttribute(k_chain, cudaFuncAttributeMaxDynamicSharedMemorySize, C_SMEM);
    }
    ChainMaps cm; SideMaps sd; Sched sc;
    make_map(&sd.h, sym(g_h), S_TOK, DM, 128); make_map3(&sd.wv, Wv, DM, HD, 64, 3);
    make_map3(&sd.ost, sym(g_o), S_TOK, HD, 32, 3); make_map(&sd.o, sym(g_o), S_TOK, HD, 128, 32); make_map3(&sd.wo, Wo, HD, DM, 32, 5);
    make_map3(&sd.slab3, sym(g_slab), NSLAB * 128, DM, 64, 3); make_map3(&sd.slab2, sym(g_slab), NSLAB * 128, DM, 64, 2);
    for (int i = 0; i < 3; i++) make_map_ln(&sd.ln[i], sym(g_slab), i + 3);
    make_map(&sd.wgate, wgate, DM, FF, 128, 16); make_map(&sd.wup, wup, DM, FF, 128, 16); make_map(&sd.wdown, wdown, FF, DM, 256, 8);
    make_map(&cm.wq, Wq, DM, HD, 128); make_map(&cm.wk, Wk, DM, HD, 128); make_map(&cm.wv, Wv, DM, HD, 128); make_map3(&cm.wo, Wo, HD, DM, 32, 7, 32);
    make_map3(&cm.h1, sym(g_h), S_TOK, DM, 32, 1); make_map3(&cm.h4, sym(g_h), S_TOK, DM, 32, 4);
    make_map(&cm.wmod, wmod, DM, 6 * DM, 160, 16);
    ChainArgs ar = {x, mem0, c, 650, 100, 0, {2, 9, 3, 0}};
    const char *order = "V0V1V2T7V3V4V5O0V6O1V7O2V8O3V9O4VaO5VbO6VcO7VdO8VeO9VfOaObOcT2OdOeOfLeLf",
               *lsplit = "2222222222333445";
    make_sched(&sc, order, lsplit);
    k_chain<<<96, 384, C_SMEM>>>(cm, ar);
    cudaLaunchConfig_t cfg = {};
    cfg.gridDim = dim3(N_SIDE); cfg.blockDim = dim3(512); cfg.dynamicSmemBytes = SD_SMEM; cfg.stream = cudaStreamPerThread;
    cudaLaunchAttribute at[1]; at[0].id = cudaLaunchAttributeProgrammaticStreamSerialization; at[0].val.programmaticStreamSerializationAllowed = 1;
    cfg.attrs = at; cfg.numAttrs = 1;
    cudaLaunchKernelEx(&cfg, k_side, sd, sc, x, wr, c, wmod, out);
}
```

```cpp
#include <cuda_runtime.h>
#include <cuda_bf16.h>
#include <cuda.h>
#include <stdint.h>
#include <stdio.h>
#include <string.h>
#include <stdlib.h>

typedef __nv_bfloat16 bf16;
constexpr int S_TOK = 2048, DM = 640, NH = 32, DH = 192, HD = NH * DH, NSEG = 64, SEG = 32, FF = 1536;

__device__ bf16 g_mod[6 * DM];
__device__ __align__(128) uint32_t g_modt[2 * DM];
__device__ bf16 g_h[S_TOK * DM];
constexpr int REC = 43008, R_Q = 12288, R_K = R_Q + 4096, R_KM = R_Q + 8192, R_VM = R_Q + 9216, R_J = 10240;
__device__ __align__(1024) uint8_t g_rec[(size_t)NSEG * NH * REC];
__host__ __device__ constexpr uint32_t vswz(uint32_t t) { return (t ^ (t >> 3 << 1)) & 7; }
__device__ bf16 g_o[S_TOK * HD];
__device__ bf16 g_x1[S_TOK * DM];
__device__ bf16 g_h2[S_TOK * DM];
__device__ bf16 g_r[S_TOK];
__device__ __align__(128) uint32_t g_gu[FF / 8 * 32];
__device__ __align__(1024) uint8_t g_acc[32 * 32768];
__device__ float g_slow[2 * NH * 20 * 32 * 8];
constexpr int NSLAB = 192;
__device__ bf16 g_slab[NSLAB * 128 * DM];
struct __align__(128) Flags {
    uint32_t v[16 * 32];
    uint32_t seg[64 * 32];
    uint32_t at[32 * 32];
    uint32_t o[32 * 32];
    uint32_t ln[16 * 32];
    uint32_t gu, pad1[31], slow, mod, pad3[30], anext, pad6[31], bnext, pad7[31];
    uint32_t h, pad4[31], done, pad5[31], next, pad2[31];
};
__device__ Flags g_flags;

__device__ __forceinline__ uint32_t smem_u32(const void* p) { return (uint32_t)__cvta_generic_to_shared(p); }
__device__ __forceinline__ uint32_t pack2(float lo, float hi) {
    uint32_t r; asm("cvt.rn.bf16x2.f32 %0, %1, %2;" : "=r"(r) : "f"(hi), "f"(lo)); return r;
}
__device__ __forceinline__ float bfr(float x) { return __uint_as_float(pack2(0.f, x)); }
__device__ __forceinline__ float inv_std(float var) {
    float s, r; asm("sqrt.approx.f32 %0, %1;" : "=f"(s) : "f"(bfr(bfr(var) + 1e-5f))); asm("rcp.approx.f32 %0, %1;" : "=f"(r) : "f"(bfr(s))); return r;
}
__device__ __forceinline__ float lo_f(uint32_t v) { return __uint_as_float(v << 16); }
__device__ __forceinline__ float hi_f(uint32_t v) { return __uint_as_float(v & 0xffff0000u); }
__device__ __forceinline__ void mbar_init(uint32_t bar, int cnt) { asm volatile("mbarrier.init.shared::cta.b64 [%0], %1;" :: "r"(bar), "r"(cnt) : "memory"); }
__device__ __forceinline__ void mbar_expect(uint32_t bar, int bytes) { asm volatile("mbarrier.arrive.expect_tx.shared::cta.b64 _, [%0], %1;" :: "r"(bar), "r"(bytes) : "memory"); }
__device__ __forceinline__ void mbar_arrive(uint32_t bar) { asm volatile("mbarrier.arrive.shared::cta.b64 _, [%0];" :: "r"(bar) : "memory"); }
constexpr int SPIN_LIMIT = 1 << 18;
__device__ __forceinline__ void mbar_wait(uint32_t bar, uint32_t par) {
    asm volatile("{ .reg .pred p, q; .reg .u32 n; mov.u32 n, 0;\n"
                 "W_%=: mbarrier.try_wait.parity.shared::cta.b64 p, [%0], %1;\n"
                 "@p bra.uni D_%=;\n"
                 "add.u32 n, n, 1; setp.lt.u32 q, n, 0x200000; @q bra.uni W_%=;\n"
                 "trap;\n"
                 "D_%=: }" :: "r"(bar), "r"(par) : "memory");
}
__device__ __forceinline__ bool mbar_test(uint32_t bar, uint32_t par) {
    uint32_t ok; asm volatile("{ .reg .pred p; mbarrier.test_wait.parity.shared::cta.b64 p, [%1], %2; selp.u32 %0, 1, 0, p; }" : "=r"(ok) : "r"(bar), "r"(par) : "memory"); return ok;
}
__device__ __forceinline__ void tma2d(uint32_t dst, const CUtensorMap* m, int c0, int c1, uint32_t bar) {
    asm volatile("cp.async.bulk.tensor.2d.shared::cluster.global.mbarrier::complete_tx::bytes [%0], [%1, {%3, %4}], [%2];"
        :: "r"(dst), "l"((uint64_t)m), "r"(bar), "r"(c0), "r"(c1) : "memory");
}
__device__ __forceinline__ uint64_t policy_stream() { uint64_t p; asm("createpolicy.fractional.L2::evict_first.b64 %0, 1.0;" : "=l"(p)); return p; }
__device__ __forceinline__ void tma2d_ef(uint32_t dst, const CUtensorMap* m, int c0, int c1, uint32_t bar, uint64_t pol) {
    asm volatile("cp.async.bulk.tensor.2d.shared::cluster.global.mbarrier::complete_tx::bytes.L2::cache_hint [%0], [%1, {%3, %4}], [%2], %5;"
        :: "r"(dst), "l"((uint64_t)m), "r"(bar), "r"(c0), "r"(c1), "l"(pol) : "memory");
}
__device__ __forceinline__ void tma3d(uint32_t dst, const CUtensorMap* m, int row, int chunk, uint32_t bar) {
    asm volatile("cp.async.bulk.tensor.3d.shared::cluster.global.mbarrier::complete_tx::bytes [%0], [%1, {0, %3, %4}], [%2];"
        :: "r"(dst), "l"((uint64_t)m), "r"(bar), "r"(row), "r"(chunk) : "memory");
}
__device__ __forceinline__ void tma3d_store(const CUtensorMap* m, int row, int chunk, uint32_t src, uint64_t pol, bool hint) {
    if (hint) asm volatile("cp.async.bulk.tensor.3d.global.shared::cta.bulk_group.L2::cache_hint [%0, {0, %2, %3}], [%1], %4;"
        :: "l"((uint64_t)m), "r"(src), "r"(row), "r"(chunk), "l"(pol) : "memory");
    else asm volatile("cp.async.bulk.tensor.3d.global.shared::cta.bulk_group [%0, {0, %2, %3}], [%1];"
        :: "l"((uint64_t)m), "r"(src), "r"(row), "r"(chunk) : "memory");
}
__device__ __forceinline__ bool elect() { uint32_t p; asm volatile("{ .reg .pred e; elect.sync _|e, -1; selp.u32 %0, 1, 0, e; }" : "=r"(p)); return p; }
__device__ __forceinline__ uint2 ld_ef(const void* p, uint64_t pol) {
    uint2 v; asm volatile("ld.relaxed.gpu.global.L2::cache_hint.v2.u32 {%0,%1}, [%2], %3;" : "=r"(v.x), "=r"(v.y) : "l"(p), "l"(pol)); return v;
}
__device__ __forceinline__ void st_ef(void* p, uint2 v, uint64_t pol) {
    asm volatile("st.global.L2::cache_hint.v2.u32 [%0], {%1,%2}, %3;" :: "l"(p), "r"(v.x), "r"(v.y), "l"(pol) : "memory");
}
__device__ __forceinline__ void bulk_g2s(uint32_t dst, const void* src, int bytes, uint32_t bar) {
    asm volatile("cp.async.bulk.shared::cluster.global.mbarrier::complete_tx::bytes [%0], [%1], %2, [%3];" :: "r"(dst), "l"(src), "r"(bytes), "r"(bar) : "memory");
}
__device__ __forceinline__ void bulk_g2s_ef(uint32_t dst, const void* src, int bytes, uint32_t bar, uint64_t pol) {
    asm volatile("cp.async.bulk.shared::cluster.global.mbarrier::complete_tx::bytes.L2::cache_hint [%0], [%1], %2, [%3], %4;" :: "r"(dst), "l"(src), "r"(bytes), "r"(bar), "l"(pol) : "memory");
}
__device__ __forceinline__ void bulk_s2g(void* dst, uint32_t src, int bytes) {
    asm volatile("cp.async.bulk.global.shared::cta.bulk_group [%0], [%1], %2;" :: "l"(dst), "r"(src), "r"(bytes) : "memory");
}
__device__ __forceinline__ void bulk_s2g_ef(void* dst, uint32_t src, int bytes, uint64_t pol) {
    asm volatile("cp.async.bulk.global.shared::cta.bulk_group.L2::cache_hint [%0], [%1], %2, %3;" :: "l"(dst), "r"(src), "r"(bytes), "l"(pol) : "memory");
}
#define EF 31
#define BULK_COMMIT()    asm volatile("cp.async.bulk.commit_group;" ::: "memory")
#define BULK_WAIT_READ() asm volatile("cp.async.bulk.wait_group.read 0;" ::: "memory")
#define BULK_WAIT()      asm volatile("cp.async.bulk.wait_group 0;" ::: "memory")
#define PROXY_FENCE()    asm volatile("fence.proxy.async.shared::cta;" ::: "memory")
__device__ __forceinline__ void ldsm4(uint32_t (&r)[4], uint32_t a) {
    asm volatile("ldmatrix.sync.aligned.m8n8.x4.shared.b16 {%0,%1,%2,%3}, [%4];" : "=r"(r[0]), "=r"(r[1]), "=r"(r[2]), "=r"(r[3]) : "r"(a) : "memory");
}
__device__ __forceinline__ void ldsm4t(uint32_t (&r)[4], uint32_t a) {
    asm volatile("ldmatrix.sync.aligned.m8n8.x4.trans.shared.b16 {%0,%1,%2,%3}, [%4];" : "=r"(r[0]), "=r"(r[1]), "=r"(r[2]), "=r"(r[3]) : "r"(a) : "memory");
}
__device__ __forceinline__ void stsm4(uint32_t a, uint32_t r0, uint32_t r1, uint32_t r2, uint32_t r3) {
    asm volatile("stmatrix.sync.aligned.m8n8.x4.shared.b16 [%0], {%1,%2,%3,%4};" :: "r"(a), "r"(r0), "r"(r1), "r"(r2), "r"(r3) : "memory");
}
__device__ __forceinline__ uint32_t movm_t(uint32_t v) { uint32_t r; asm volatile("movmatrix.sync.aligned.m8n8.trans.b16 %0, %1;" : "=r"(r) : "r"(v)); return r; }
__device__ __forceinline__ void mma16(float (&d)[4], uint32_t a0, uint32_t a1, uint32_t a2, uint32_t a3, uint32_t b0, uint32_t b1) {
    asm volatile("mma.sync.aligned.m16n8k16.row.col.f32.bf16.bf16.f32 {%0,%1,%2,%3}, {%4,%5,%6,%7}, {%8,%9}, {%0,%1,%2,%3};"
        : "+f"(d[0]), "+f"(d[1]), "+f"(d[2]), "+f"(d[3]) : "r"(a0), "r"(a1), "r"(a2), "r"(a3), "r"(b0), "r"(b1));
}
__device__ __forceinline__ void mma16(float (&d)[4], const uint32_t (&a)[4], uint32_t b0, uint32_t b1) { mma16(d, a[0], a[1], a[2], a[3], b0, b1); }
__device__ __forceinline__ void mma16z(float (&d)[4], const uint32_t (&a)[4], uint32_t b0, uint32_t b1) {
    asm volatile("mma.sync.aligned.m16n8k16.row.col.f32.bf16.bf16.f32 {%0,%1,%2,%3}, {%4,%5,%6,%7}, {%8,%9}, {%10,%10,%10,%10};"
        : "=f"(d[0]), "=f"(d[1]), "=f"(d[2]), "=f"(d[3]) : "r"(a[0]), "r"(a[1]), "r"(a[2]), "r"(a[3]), "r"(b0), "r"(b1), "f"(0.f));
}
__device__ __forceinline__ void mma8z(float (&d)[4], uint32_t a0, uint32_t a1, uint32_t b0) {
    asm volatile("mma.sync.aligned.m16n8k8.row.col.f32.bf16.bf16.f32 {%0,%1,%2,%3}, {%4,%5}, {%6}, {%7,%7,%7,%7};"
        : "=f"(d[0]), "=f"(d[1]), "=f"(d[2]), "=f"(d[3]) : "r"(a0), "r"(a1), "r"(b0), "f"(0.f));
}
__device__ __forceinline__ void bar_sync(int id, int n) { asm volatile("bar.sync %0, %1;" :: "r"(id), "r"(n) : "memory"); }
__device__ __forceinline__ void bar_arrive(int id, int n) { asm volatile("bar.arrive %0, %1;" :: "r"(id), "r"(n) : "memory"); }
__device__ __forceinline__ uint64_t mkdesc(uint32_t addr, uint32_t lbo, uint32_t sbo) {
    return (uint64_t)((addr & 0x3FFFF) >> 4) | ((uint64_t)(lbo >> 4) << 16) | ((uint64_t)(sbo >> 4) << 32) | (1ull << 62);
}
#define WG_FENCE()  asm volatile("wgmma.fence.sync.aligned;" ::: "memory")
#define WG_COMMIT() asm volatile("wgmma.commit_group.sync.aligned;" ::: "memory")
#define WG_WAIT(n)  asm volatile("wgmma.wait_group.sync.aligned %0;" :: "n"(n) : "memory")

__device__ __forceinline__ void wgmma_ss_n192_tb(float (&d)[96], uint64_t a, uint64_t b, int acc) {
    asm volatile("{ .reg .pred p; setp.ne.b32 p, %98, 0;\n"
        "wgmma.mma_async.sync.aligned.m64n192k16.f32.bf16.bf16 {%0,%1,%2,%3,%4,%5,%6,%7,%8,%9,%10,%11,%12,%13,%14,%15,%16,%17,%18,%19,%20,%21,%22,%23,%24,%25,%26,%27,%28,%29,%30,%31,%32,%33,%34,%35,%36,%37,%38,%39,%40,%41,%42,%43,%44,%45,%46,%47,%48,%49,%50,%51,%52,%53,%54,%55,%56,%57,%58,%59,%60,%61,%62,%63,%64,%65,%66,%67,%68,%69,%70,%71,%72,%73,%74,%75,%76,%77,%78,%79,%80,%81,%82,%83,%84,%85,%86,%87,%88,%89,%90,%91,%92,%93,%94,%95}, %96, %97, p, 1, 1, 0, 1; }"
        : "+f"(d[0]), "+f"(d[1]), "+f"(d[2]), "+f"(d[3]), "+f"(d[4]), "+f"(d[5]), "+f"(d[6]), "+f"(d[7]), "+f"(d[8]), "+f"(d[9]), "+f"(d[10]), "+f"(d[11]), "+f"(d[12]), "+f"(d[13]), "+f"(d[14]), "+f"(d[15]), "+f"(d[16]), "+f"(d[17]), "+f"(d[18]), "+f"(d[19]), "+f"(d[20]), "+f"(d[21]), "+f"(d[22]), "+f"(d[23]), "+f"(d[24]), "+f"(d[25]), "+f"(d[26]), "+f"(d[27]), "+f"(d[28]), "+f"(d[29]), "+f"(d[30]), "+f"(d[31]), "+f"(d[32]), "+f"(d[33]), "+f"(d[34]), "+f"(d[35]), "+f"(d[36]), "+f"(d[37]), "+f"(d[38]), "+f"(d[39]), "+f"(d[40]), "+f"(d[41]), "+f"(d[42]), "+f"(d[43]), "+f"(d[44]), "+f"(d[45]), "+f"(d[46]), "+f"(d[47]), "+f"(d[48]), "+f"(d[49]), "+f"(d[50]), "+f"(d[51]), "+f"(d[52]), "+f"(d[53]), "+f"(d[54]), "+f"(d[55]), "+f"(d[56]), "+f"(d[57]), "+f"(d[58]), "+f"(d[59]), "+f"(d[60]), "+f"(d[61]), "+f"(d[62]), "+f"(d[63]), "+f"(d[64]), "+f"(d[65]), "+f"(d[66]), "+f"(d[67]), "+f"(d[68]), "+f"(d[69]), "+f"(d[70]), "+f"(d[71]), "+f"(d[72]), "+f"(d[73]), "+f"(d[74]), "+f"(d[75]), "+f"(d[76]), "+f"(d[77]), "+f"(d[78]), "+f"(d[79]), "+f"(d[80]), "+f"(d[81]), "+f"(d[82]), "+f"(d[83]), "+f"(d[84]), "+f"(d[85]), "+f"(d[86]), "+f"(d[87]), "+f"(d[88]), "+f"(d[89]), "+f"(d[90]), "+f"(d[91]), "+f"(d[92]), "+f"(d[93]), "+f"(d[94]), "+f"(d[95])
        : "l"(a), "l"(b), "r"(acc));
}

__device__ __forceinline__ void wgmma_ss_n128_tb(float (&d)[64], uint64_t a, uint64_t b, int acc) {
    asm volatile("{ .reg .pred p; setp.ne.b32 p, %66, 0;\n"
        "wgmma.mma_async.sync.aligned.m64n128k16.f32.bf16.bf16 {%0,%1,%2,%3,%4,%5,%6,%7,%8,%9,%10,%11,%12,%13,%14,%15,%16,%17,%18,%19,%20,%21,%22,%23,%24,%25,%26,%27,%28,%29,%30,%31,%32,%33,%34,%35,%36,%37,%38,%39,%40,%41,%42,%43,%44,%45,%46,%47,%48,%49,%50,%51,%52,%53,%54,%55,%56,%57,%58,%59,%60,%61,%62,%63}, %64, %65, p, 1, 1, 0, 1; }"
        : "+f"(d[0]), "+f"(d[1]), "+f"(d[2]), "+f"(d[3]), "+f"(d[4]), "+f"(d[5]), "+f"(d[6]), "+f"(d[7]), "+f"(d[8]), "+f"(d[9]), "+f"(d[10]), "+f"(d[11]), "+f"(d[12]), "+f"(d[13]), "+f"(d[14]), "+f"(d[15]), "+f"(d[16]), "+f"(d[17]), "+f"(d[18]), "+f"(d[19]), "+f"(d[20]), "+f"(d[21]), "+f"(d[22]), "+f"(d[23]), "+f"(d[24]), "+f"(d[25]), "+f"(d[26]), "+f"(d[27]), "+f"(d[28]), "+f"(d[29]), "+f"(d[30]), "+f"(d[31]), "+f"(d[32]), "+f"(d[33]), "+f"(d[34]), "+f"(d[35]), "+f"(d[36]), "+f"(d[37]), "+f"(d[38]), "+f"(d[39]), "+f"(d[40]), "+f"(d[41]), "+f"(d[42]), "+f"(d[43]), "+f"(d[44]), "+f"(d[45]), "+f"(d[46]), "+f"(d[47]), "+f"(d[48]), "+f"(d[49]), "+f"(d[50]), "+f"(d[51]), "+f"(d[52]), "+f"(d[53]), "+f"(d[54]), "+f"(d[55]), "+f"(d[56]), "+f"(d[57]), "+f"(d[58]), "+f"(d[59]), "+f"(d[60]), "+f"(d[61]), "+f"(d[62]), "+f"(d[63])
        : "l"(a), "l"(b), "r"(acc));
}

__device__ __forceinline__ void wgmma_rs_n32(float (&d)[16], const uint32_t (&a)[4], uint64_t b) {
    asm volatile("wgmma.mma_async.sync.aligned.m64n32k16.f32.bf16.bf16 {%0,%1,%2,%3,%4,%5,%6,%7,%8,%9,%10,%11,%12,%13,%14,%15}, {%16,%17,%18,%19}, %20, 1, 1, 1, 0;"
        : "+f"(d[0]), "+f"(d[1]), "+f"(d[2]), "+f"(d[3]), "+f"(d[4]), "+f"(d[5]), "+f"(d[6]), "+f"(d[7]), "+f"(d[8]), "+f"(d[9]), "+f"(d[10]), "+f"(d[11]), "+f"(d[12]), "+f"(d[13]), "+f"(d[14]), "+f"(d[15])
        : "r"(a[0]), "r"(a[1]), "r"(a[2]), "r"(a[3]), "l"(b));
}
__device__ __forceinline__ uint32_t umax3(uint32_t a, uint32_t b, uint32_t c) { return max(max(a, b), c); }
__device__ __forceinline__ void wait_until(uint32_t t) { while ((int32_t)((uint32_t)clock() - t) < 0) {} }
__device__ __forceinline__ uint32_t gtime() { uint32_t c; asm volatile("mov.u32 %0, %%globaltimer_lo;" : "=r"(c)); return c; }
__device__ __forceinline__ uint32_t opaque(uint32_t v) { uint32_t r; asm volatile("shfl.sync.bfly.b32 %0, %1, 0, 31, -1;" : "=r"(r) : "r"(v)); return r; }
__device__ __forceinline__ uint32_t lds32(uint32_t a) { uint32_t v; asm volatile("ld.shared.u32 %0, [%1];" : "=r"(v) : "r"(a) : "memory"); return v; }
__device__ __forceinline__ void sts32(uint32_t a, uint32_t v) { asm volatile("st.shared.u32 [%0], %1;" :: "r"(a), "r"(v) : "memory"); }
__device__ __forceinline__ void lds64(uint32_t (&v)[2], uint32_t a) { asm volatile("ld.shared.v2.u32 {%0,%1}, [%2];" : "=r"(v[0]), "=r"(v[1]) : "r"(a) : "memory"); }
__device__ __forceinline__ void lds128(uint32_t (&v)[4], uint32_t a) { asm volatile("ld.shared.v4.u32 {%0,%1,%2,%3}, [%4];" : "=r"(v[0]), "=r"(v[1]), "=r"(v[2]), "=r"(v[3]) : "r"(a) : "memory"); }
__device__ __forceinline__ void sts128(uint32_t a, uint32_t x, uint32_t y, uint32_t z, uint32_t w) { asm volatile("st.shared.v4.u32 [%0], {%1,%2,%3,%4};" :: "r"(a), "r"(x), "r"(y), "r"(z), "r"(w) : "memory"); }
__device__ __forceinline__ float2 lds64f(uint32_t a) { float2 v; asm volatile("ld.shared.v2.f32 {%0,%1}, [%2];" : "=f"(v.x), "=f"(v.y) : "r"(a) : "memory"); return v; }
__device__ __forceinline__ float4 lds128f(uint32_t a) { float4 v; asm volatile("ld.shared.v4.f32 {%0,%1,%2,%3}, [%4];" : "=f"(v.x), "=f"(v.y), "=f"(v.z), "=f"(v.w) : "r"(a) : "memory"); return v; }
__device__ __forceinline__ void sts128f(uint32_t a, float x, float y, float z, float w) { asm volatile("st.shared.v4.f32 [%0], {%1,%2,%3,%4};" :: "r"(a), "f"(x), "f"(y), "f"(z), "f"(w) : "memory"); }

__device__ __forceinline__ float warp_sum(float v) {
#pragma unroll
    for (int o = 16; o; o >>= 1) v += __shfl_xor_sync(0xffffffffu, v, o);
    return v;
}
__device__ __forceinline__ uint32_t badd(uint32_t a, uint32_t b) { uint32_t r; asm("add.rn.bf16x2 %0, %1, %2;" : "=r"(r) : "r"(a), "r"(b)); return r; }
__device__ __forceinline__ uint32_t bsub(uint32_t a, uint32_t b) { uint32_t r; asm("sub.rn.bf16x2 %0, %1, %2;" : "=r"(r) : "r"(a), "r"(b)); return r; }
__device__ __forceinline__ uint32_t bmul(uint32_t a, uint32_t b) { uint32_t r; asm("mul.rn.bf16x2 %0, %1, %2;" : "=r"(r) : "r"(a), "r"(b)); return r; }
__device__ __forceinline__ uint32_t silu2(uint32_t v) { return pack2(__fdividef(lo_f(v), 1.f + __expf(-lo_f(v))), __fdividef(hi_f(v), 1.f + __expf(-hi_f(v)))); }
__device__ __forceinline__ void ln_row(const uint32_t (&x)[10], uint32_t (&n)[10]) {
    float s0 = 0, s1 = 0;
#pragma unroll
    for (int i = 0; i < 10; i++) { s0 += lo_f(x[i]); s1 += hi_f(x[i]); }
    const float mean = warp_sum(s0 + s1) * (1.f / DM);
    float q0 = 0, q1 = 0;
#pragma unroll
    for (int i = 0; i < 10; i++) { const float d0 = lo_f(x[i]) - mean, d1 = hi_f(x[i]) - mean; q0 += d0 * d0; q1 += d1 * d1; }
    const uint32_t mb = pack2(mean, mean);
    const float inv = inv_std(warp_sum(q0 + q1) * (1.f / DM));
#pragma unroll
    for (int i = 0; i < 10; i++) { const uint32_t d = bsub(x[i], mb); n[i] = pack2(lo_f(d) * inv, hi_f(d) * inv); }
}
__device__ __forceinline__ uint32_t ld_rlx(const uint32_t* f) { uint32_t v; asm volatile("ld.relaxed.gpu.global.u32 %0, [%1];" : "=r"(v) : "l"(f) : "memory"); return v; }
__device__ __forceinline__ void flag_wait(const uint32_t* f, uint32_t target) {
    for (int n = 0;; n++) {
        uint32_t v; asm volatile("ld.relaxed.gpu.global.u32 %0, [%1];" : "=r"(v) : "l"(f) : "memory");
        if (v >= target) break;
        if (n > (1 << 23)) __trap();
    }
}
__device__ __forceinline__ void flag_wait_warp(const uint32_t* f, uint32_t target) {
    for (int n = 0; !__all_sync(0xffffffffu, ld_rlx(f) >= target); n++) if (n > (1 << 23)) __trap();
}
__device__ __forceinline__ void flag_add(uint32_t* f, uint32_t v = 1) { asm volatile("red.release.gpu.global.add.u32 [%0], %1;" :: "l"(f), "r"(v) : "memory"); }
constexpr int N_SIDE = 132;
__device__ __forceinline__ void flags_release() {
    uint32_t old; asm volatile("atom.acq_rel.gpu.global.add.u32 %0, [%1], 1;" : "=r"(old) : "l"(&g_flags.done) : "memory");
    if (old == 96 + N_SIDE - 1) { g_flags.h = 0; g_flags.next = 0; g_flags.done = 0; }
}

struct ChainMaps { CUtensorMap wq, wk, wv, wo, h1, h4, wmod; };
struct ChainArgs { const bf16 *x, *mem0, *c; int D, D2, force, P[4]; };
constexpr uint32_t SM_BASE = 1024;
constexpr int C_WV = 0, C_WO = 81920, C_XR = 167936, C_QX = C_XR + 4 * 4096, C_KX = C_XR + 9 * 4096, C_VX = C_XR + 40960, C_MEM = C_VX + 4096, C_VP = C_MEM,
              C_QM = C_MEM + 10240, C_KM = C_QM + 1024, C_VM = C_KM + 1024, C_OX = C_VM + 1024, C_SC = C_OX + 3072, C_BAR = C_SC + 1920, C_SMEM = C_BAR + 256;
constexpr int CB_W = C_BAR, CB_W2 = C_BAR + 8, CB_SC = C_BAR + 16, CB_OX = C_BAR + 24, CB_VX = C_BAR + 32, CB_XF = C_BAR + 40, CB_XG = C_BAR + 48, CB_PRE = C_BAR + 56, CB_WK = C_BAR + 64, CB_PC = C_BAR + 96,
              C_MAX = C_BAR + 128, C_SCL = C_BAR + 144, C_BAD = C_BAR + 148;
static_assert(C_SMEM <= 232448, "chain shared memory");
enum { B_MEM = 1, B_QK, B_VP, B_OWN, B_RED, B_X, B_AUX, B_VM };
constexpr int NP = 8;
constexpr int NW = 8;
#define VD 2
#define VPB 4
#define VPRE 1
#define BX 3
constexpr int OD = 4;
#define PROF(i)
#define PROFG(i)
#define PROFV(i, v)
#define SFENCE() asm volatile("griddepcontrol.launch_dependents;" ::: "memory")
#define PIN(x) asm volatile("" : "+r"(x))
#define PINL(x) asm volatile("" : "+l"(x))
__host__ __device__ constexpr bool pair_v(int i) { return i == 0 || (i % 3 == 2 && i < 9); }
__host__ __device__ constexpr bool pair_own(int i) { return pair_v(i) || i >= 14; }
__host__ __device__ constexpr int pair_idx(int i) { return pair_v(i) ? (i + 1) / 3 : i < 14 ? i - (i < 9 ? i / 3 + 1 : 4) : i - 10; }
__host__ __device__ constexpr int pair_ld(int i) { return i + 2 + (i / 3 < BX ? i / 3 : BX) < 20 ? i + 2 + (i / 3 < BX ? i / 3 : BX) : 20; }

__device__ __forceinline__ uint32_t packh(float lo, float hi) { uint32_t r; asm("cvt.rn.f16x2.f32 %0, %1, %2;" : "=r"(r) : "f"(hi), "f"(lo)); return r; }
__device__ __forceinline__ uint32_t h2b(uint32_t v) {
    uint32_t r; asm("{ .reg .f16 a, b; .reg .f32 x, y; mov.b32 {a, b}, %1; cvt.f32.f16 x, a; cvt.f32.f16 y, b; cvt.rn.bf16x2.f32 %0, y, x; }" : "=r"(r) : "r"(v)); return r;
}
__device__ __forceinline__ uint32_t h2b_lo(uint32_t u, uint32_t v) {
    uint32_t r; asm("{ .reg .f16 a, b, c, d; .reg .f32 x, y; mov.b32 {a, b}, %1; mov.b32 {c, d}, %2; cvt.f32.f16 x, a; cvt.f32.f16 y, c; cvt.rn.bf16x2.f32 %0, y, x; }" : "=r"(r) : "r"(u), "r"(v)); return r;
}
constexpr float SCL2E = 0.07216878364870322f * 1.4426950408889634f;
__device__ __forceinline__ uint32_t score_tile(const uint32_t (&qa)[2][4], const uint32_t (&kb)[2][4]) {
    float u[4], v[4], x[4], y[4];
    mma16z(u, qa[0], kb[0][0], kb[0][1]); mma16z(v, qa[0], kb[0][2], kb[0][3]);
    mma16z(x, qa[1], kb[1][0], kb[1][1]); mma16z(y, qa[1], kb[1][2], kb[1][3]);
    return pack2(((u[0] + v[2]) + (x[0] + y[2])) * SCL2E, ((u[1] + v[3]) + (x[1] + y[3])) * SCL2E);
}
__device__ __forceinline__ void score_tiles(const uint32_t (&qa)[2][4], const uint32_t (&kb)[2][4], const uint32_t (&km)[2][4], uint32_t& a, uint32_t& b) {
    float u[4], v[4], x[4], y[4];
    mma16z(u, qa[0], kb[0][0], kb[0][1]); mma16z(v, qa[0], kb[0][2], kb[0][3]); mma16z(x, qa[0], km[0][0], km[0][1]); mma16z(y, qa[0], km[0][2], km[0][3]);
    mma16(u, qa[1], kb[1][0], kb[1][1]); mma16(v, qa[1], kb[1][2], kb[1][3]); mma16(x, qa[1], km[1][0], km[1][1]); mma16(y, qa[1], km[1][2], km[1][3]);
    a = pack2((u[0] + v[2]) * SCL2E, (u[1] + v[3]) * SCL2E); b = pack2((x[0] + y[2]) * SCL2E, (x[1] + y[3]) * SCL2E);
}
__device__ __forceinline__ void stas1(uint32_t dst, uint32_t x, uint32_t bar) {
    asm volatile("st.async.shared::cluster.mbarrier::complete_tx::bytes.b32 [%0], %1, [%2];" :: "r"(dst), "r"(x), "r"(bar) : "memory");
}
__device__ __forceinline__ void stas2(uint32_t dst, uint32_t x, uint32_t y, uint32_t bar) {
    asm volatile("st.async.shared::cluster.mbarrier::complete_tx::bytes.v2.b32 [%0], {%1,%2}, [%3];" :: "r"(dst), "r"(x), "r"(y), "r"(bar) : "memory");
}
__device__ __forceinline__ float ex2(float x) { float r; asm volatile("ex2.approx.ftz.f32 %0, %1;" : "=f"(r) : "f"(x)); return r; }
__device__ __forceinline__ void h_fetch_a(const ChainMaps& mp, uint32_t sm, int n) {
    mbar_expect(sm + CB_XF, 32768);
    tma3d(sm + C_XR, &mp.h4, n * SEG, 0, sm + CB_XF); tma3d(sm + C_XR + 20480, &mp.h4, n * SEG, 5, sm + CB_XF);
}
__device__ __forceinline__ void h_fetch_b(const ChainMaps& mp, uint32_t sm, int n) {
    mbar_expect(sm + CB_XG, 8192);
    tma3d(sm + C_QX, &mp.h1, n * SEG, 4, sm + CB_XG); tma3d(sm + C_KX, &mp.h1, n * SEG, 9, sm + CB_XG);
}
__device__ __forceinline__ uint32_t absmax2(uint32_t a, uint32_t b) {
    uint32_t r; asm("max.u16x2 %0, %1, %2;" : "=r"(r) : "r"(a), "r"(b & 0x7fff7fffu)); return r;
}

__global__ void __cluster_dims__(3, 1, 1) __launch_bounds__(384, 1) k_chain(const __grid_constant__ ChainMaps mp, const __grid_constant__ ChainArgs ar) {
    extern __shared__ __align__(1024) uint8_t smraw[];
    const uint32_t sm = SM_BASE + ((blockIdx.x % 3) << 24);
    if (smem_u32(smraw) != sm) __trap();
    uint32_t tid; asm volatile("mov.u32 %0, %%tid.x;" : "=r"(tid));
    const int warp = __shfl_sync(0xffffffffu, tid >> 5, 0), lane = tid & 31, wg = warp >> 2, w = warp & 3;
    const int blk = blockIdx.x, head = blk / 3, j = blk % 3;
    const int col0 = head * DH + j * 64, u0 = 7 * j, nu = j == 2 ? 6 : 7;
    asm volatile("griddepcontrol.launch_dependents;");
#define PPROF(i)
#define PPROF2(i)
    PPROF(0);
    const int r = lane & 7, mi = lane >> 3;
    {
        if (warp == 11) {
            if (lane < 16) mbar_init(sm + C_BAR + 8 * lane, lane == 2 ? 5 : 1);
            asm volatile("fence.mbarrier_init.release.cluster;" ::: "memory");
            __syncwarp();
            if (elect()) {
                mbar_expect(sm + CB_PRE, (blk < 80 ? 20480 : 0) + 10240);
                if (blk < 80) {
#pragma unroll 1
                    for (int c = 0; c < 4; c++) tma2d(sm + C_XR + c * 5120, &mp.wmod, blk * 16, c * 160, sm + CB_PRE);
                }
                bulk_g2s(sm + C_XR + 20480, ar.mem0, 10240, sm + CB_PRE);
                mbar_expect(sm + CB_SC, 1280); mbar_expect(sm + CB_OX, 2048);
            }
            __syncwarp();
            asm volatile("barrier.cluster.arrive.relaxed.aligned; barrier.cluster.wait.aligned;" ::: "memory");
        } else {
        const int row0 = blk * 11 + warp; const bool two = row0 < S_TOK - 1056;
        uint32_t xv[2][10], cv[8];
#pragma unroll
        for (int i = 0; i < 8; i++) cv[i] = __ldg((const uint32_t*)ar.c + (warp < 10 ? warp : 0) * 32 + i * 4 + (lane & 3));
#pragma unroll
        for (int i = 0; i < 10; i++) {
            const uint2 v = __ldg((const uint2*)(ar.x + (row0 + (i >= 5 && two ? 1056 : 0)) * DM) + lane + i % 5 * 32);
            xv[i / 5][2 * (i % 5)] = v.x; xv[i / 5][2 * (i % 5) + 1] = v.y;
        }
        asm volatile("barrier.cluster.arrive.relaxed.aligned;" ::: "memory");
#pragma unroll 1
        for (int i = blk * 352 + tid; i < 32 * 1600; i += 96 * 352) ((uint4*)g_acc)[i / 1600 * 2048 + i % 1600] = make_uint4(0, 0, 0, 0);
        if (tid < 16 && blk * 16 + tid < (int)(offsetof(Flags, h) / 16)) ((uint4*)&g_flags)[blk * 16 + tid] = make_uint4(0, 0, 0, 0);
        static_assert(offsetof(Flags, h) <= 96 * 16 * 16, "flags");
        PPROF(8);
        asm volatile("barrier.cluster.wait.aligned;" ::: "memory");
        PPROF(9);
#pragma unroll
        for (int i = 0; i < 8; i++) cv[i] = silu2(cv[i]);
        mbar_wait(sm + CB_PRE, 0);
        PPROF(10);
        if (warp < 10) {
            float d[4] = {0, 0, 0, 0};
#pragma unroll
            for (int k = 0; k < 4; k++) { uint32_t a[4]; ldsm4t(a, sm + C_XR + ((warp * 4 + k) * 16 + (mi >> 1) * 8 + r) * 32 + (mi & 1) * 16); mma16(d, a, cv[2 * k], cv[2 * k + 1]); }
            if ((lane & 3) == 0) { sts32(sm + C_QM + warp * 64 + lane, __float_as_uint(d[0])); sts32(sm + C_QM + warp * 64 + 32 + lane, __float_as_uint(d[2])); }
        }
        bar_sync(B_MEM, 352);
        PPROF(11);
        if (tid < 16 && blk < 80) {
            float a = 0;
#pragma unroll
            for (int i = 0; i < 10; i++) a += __uint_as_float(lds32(sm + C_QM + i * 64 + tid * 4));
            asm volatile("st.relaxed.gpu.global.u32 [%0], %1;" :: "l"(g_modt + blk * 16 + tid), "r"(pack2(0.f, a) | 1u) : "memory");
        }
        PPROF(1);
#pragma unroll 1
        for (int q = 0; q < 2; q++) {
            uint32_t n[10]; ln_row(xv[0], n);
#pragma unroll
            for (int i = 0; i < 10; i++) { xv[0][i] = xv[1][i]; xv[1][i] = n[i]; }
        }
        if (tid < 320) {
            uint32_t v[4];
            for (int n = 0;; n++) {
                asm volatile("ld.relaxed.gpu.global.v4.u32 {%0,%1,%2,%3}, [%4];" : "=r"(v[0]), "=r"(v[1]), "=r"(v[2]), "=r"(v[3]) : "l"(g_modt + tid * 4) : "memory");
                if (__all_sync(0xffffffffu, v[0] & v[1] & v[2] & v[3] & 1)) break;
                if (n > (1 << 22)) __trap();
            }
            asm volatile("st.shared.v2.u32 [%0], {%1,%2};" :: "r"(sm + C_VX + tid * 8), "r"(__byte_perm(v[0], v[1], 0x7632)), "r"(__byte_perm(v[2], v[3], 0x7632)) : "memory");
        }
        bar_sync(B_MEM, 352);
        PPROF(2);
#pragma unroll
        for (int i = 0; i < 5; i++) {
            uint32_t sh[2], sc[2]; lds64(sh, sm + C_VX + lane * 8 + i * 256); lds64(sc, sm + C_VX + 1280 + lane * 8 + i * 256);
            sc[0] = badd(sc[0], 0x3f803f80u); sc[1] = badd(sc[1], 0x3f803f80u);
#pragma unroll
            for (int q = 0; q < 2; q++)
                if (q == 0 || two) ((uint2*)(g_h + (row0 + q * 1056) * DM))[lane + i * 32] = make_uint2(badd(bmul(xv[q][2 * i], sc[0]), sh[0]), badd(bmul(xv[q][2 * i + 1], sc[1]), sh[1]));
        }
        if (warp < 10) {
#pragma unroll
            for (int i = 0; i < 2; i++) {
                uint32_t v[4]; ldsm4t(v, sm + C_XR + 20480 + r * 1280 + ((warp * 2 + i) * 4 + mi) * 16);
                stsm4(sm + C_MEM + (warp * 2 + i) * 512 + lane * 16, v[0], v[1], v[2], v[3]);
            }
        }
        bar_sync(B_MEM, 352);
        PPROF(3);
        }
    }
    uint8_t* const rec0 = g_rec + (size_t)head * REC;
    if (wg < 2) {
        asm volatile("setmaxnreg.inc.sync.aligned.u32 224;");
        const uint32_t l16 = opaque(sm + lane * 16);
        uint32_t wa[40][4], pl[NP][4];
        const uint32_t wfrag = ((mi >> 1) * 8 + r) * 128 + (((2 * w + (mi & 1)) ^ r) << 4);
        mbar_wait(sm + (wg ? CB_WK : CB_W), 0);
#pragma unroll
        for (int i = 0; i < 40; i++)
            ldsm4t(wa[i], sm + (wg == 0 ? C_WV : C_WO) + wfrag + ((pair_own(i >> 1) ? wg : 1 - wg) * 20 + pair_idx(i >> 1) * 2 + (i & 1)) * 2048);
        PPROF(5);
        PROXY_FENCE();
        if (wg) bar_arrive(B_VM, 160); else bar_arrive(B_OWN, 160);
        const uint32_t wvrd = opaque(sm + C_WV + wfrag + wg * 40960);
        const uint32_t word = opaque(sm + C_WO + warp * 2048 + ((mi >> 1) * 8 + r) * 64 + (((mi & 1) ^ (r >> 1)) << 4));
        const uint32_t own = wg * 5120, oth = 5120 - own;
        mbar_wait(sm + CB_XF, 0);
#pragma unroll 1
        for (int s = -1;;) {
            uint64_t xo = mkdesc(SM_BASE + C_XR + wg * 20480, 16, 1024), xt = mkdesc(SM_BASE + C_XR + 20480 - wg * 20480, 16, 1024);
            if (s >= 0) {
                float dv[2][4], d[4][4], u[4], isc;
                uint32_t b[20][4], av[20][4], l4;
                const uint32_t mo = l16 + C_MEM + own, mt = l16 + C_MEM + oth;
                bar_sync(B_MEM, 384);
                if (warp == 0) { PROF(0); PROFG(24); }
#pragma unroll
                for (int i = 0; i < 20; i++) {
                    const int c = i < 3 ? 0 : (i & 1) * 2, p = 2 * pair_idx(i);
                    if (i) SFENCE();
#pragma unroll
                    for (int e = 0; e < 2; e++) { const int n = (i ? pair_ld(i - 1) : 0) + e; if (n < pair_ld(i)) ldsm4t(b[n], (pair_own(n) ? mo : mt) + pair_idx(n) * 512); }
                    if (i >= 18 - VPRE && i < 18) ldsm4t(av[NP + i - (18 - VPRE)], wvrd + (NP + i - (18 - VPRE)) * 2048);
                    if (i > 0 && pair_v(i)) { mma16(dv[0], pl[p % NP], b[i][0], b[i][1]); mma16(dv[1], pl[(p + 1) % NP], b[i][2], b[i][3]); }
                    if (i == 0 || i == 3) { mma16z(d[c], wa[2 * i], b[i][0], b[i][1]); mma16z(d[c + 1], wa[2 * i + 1], b[i][2], b[i][3]); }
                    else { mma16(d[c], wa[2 * i], b[i][0], b[i][1]); mma16(d[c + 1], wa[2 * i + 1], b[i][2], b[i][3]); }
                    if (i == 0) { mma16z(dv[0], pl[0], b[i][0], b[i][1]); mma16z(dv[1], pl[1], b[i][2], b[i][3]); }
                    if (i == 12) isc = __uint_as_float(lds32(sm + C_SCL));
                    if (i == 17) { l4 = l16; PIN(l4); l4 = (l4 >> 2) & 127; PIN(l4); }
                }
                SFENCE();
#pragma unroll
                for (int i = 0; i < 4; i++) u[i] = fmaf(d[2][i] + d[3][i], isc, (d[0][i] + d[1][i]) * isc);
                const uint32_t qs = sm + C_QM + warp * 256 + l4;
                sts32(qs, pack2(u[0], u[1])); sts32(qs + 128, pack2(u[2], u[3]));
                if (warp == 2) PROF(1);
                bar_sync(B_QK, 384);
                if (lds32(sm + C_BAD)) {
                    if (warp < nu) {
                        float e[2][4] = {{0, 0, 0, 0}, {0, 0, 0, 0}};
#pragma unroll 1
                        for (int k = 0; k < 12; k++) {
                            uint32_t ob[2]; lds64(ob, sm + C_OX + k * 256 + l4 * 2);
                            ldsm4t(pl[0], word + (k >> 1) * 14336 + (k & 1) * 1024); ldsm4t(pl[1], (word ^ 32) + (k >> 1) * 14336 + (k & 1) * 1024);
                            mma16(e[0], pl[0], ob[0], ob[1]); mma16(e[1], pl[1], ob[0], ob[1]);
                        }
                        float4* dst = (float4*)(g_slow + (((s & 1) * NH + head) * 20 + u0 + warp) * 256 + l4 * 2);
                        dst[0] = make_float4(e[0][0] * isc, e[0][1] * isc, e[0][2] * isc, e[0][3] * isc); dst[1] = make_float4(e[1][0] * isc, e[1][1] * isc, e[1][2] * isc, e[1][3] * isc);
                        __threadfence();
                    }
                    bar_arrive(B_RED, 384);
#pragma unroll
                    for (int i = 0; i < NP; i++) ldsm4t(pl[i], wvrd + i * 2048);
                    continue;
                }
                {
#pragma unroll
                    for (int f = NP + VPRE; f < NP + VPRE + VD; f++) ldsm4t(av[f], wvrd + f * 2048);
#pragma unroll
                    for (int f = NP; f < 20; f++) {
                        if (f >= NP + VPRE) SFENCE();
                        if (f >= NP + VPRE && f + VD < 20) ldsm4t(av[f + VD], wvrd + (f + VD) * 2048);
                        mma16(dv[f & 1], av[f], b[10 + (f >> 1)][2 * (f & 1)], b[10 + (f >> 1)][2 * (f & 1) + 1]);
                    }
                    sts128f(l16 + C_VP + warp * 512, (dv[0][0] + dv[1][0]) * isc, (dv[0][1] + dv[1][1]) * isc, (dv[0][2] + dv[1][2]) * isc, (dv[0][3] + dv[1][3]) * isc);
                    if (warp == 0) PROF(2);
                }
                if (warp >= nu || s + 1 == NSEG) {
                    bar_arrive(B_VP, 384);
                    PROXY_FENCE();
                    bar_arrive(B_RED, 384);
                    if (warp == 7) {
                        uint8_t* rec = rec0 + (size_t)s * (NH * REC) + j * R_J;
                        const uint64_t ef = policy_stream();
                        if (elect()) {
                            bulk_s2g_ef(rec + R_Q, sm + C_QX, 4096, ef); bulk_s2g_ef(rec + R_K, sm + C_KX, 4096, ef);
                            BULK_COMMIT();
                            if (s + 3 < NSEG) {
                                const uint8_t* ln = g_acc + ((s + 3) >> 1) * 32768 + ((s + 3) & 1) * 128 + blk * 256;
                                asm volatile("prefetch.global.L2 [%0];" :: "l"(ln) : "memory");
                                if (blk < 4) asm volatile("prefetch.global.L2 [%0];" :: "l"(ln + 96 * 256) : "memory");
                            }
                            if (s + 2 < NSEG && blk < 10) asm volatile("cp.async.bulk.prefetch.L2.global [%0], 4096;" :: "l"(g_h + (s + 2) * SEG * DM + blk * 2048) : "memory");
                        }
                        __syncwarp();
                        if (s + 1 < NSEG) {
                            bar_sync(B_VM, 160);
                            if (elect()) { BULK_WAIT_READ(); h_fetch_b(mp, sm, s + 1); }
                        } else if (elect()) { BULK_WAIT(); flag_add(&g_flags.seg[s * 32 + head]); }
                        __syncwarp();
                    }
                    if (s + 1 == NSEG) break;
                    mbar_wait(sm + CB_XF, (s + 1) & 1);
                } else {
                    uint32_t w1 = word; PIN(w1); w1 ^= 32;
                    auto frag = [&](int f) { return ((f & 1) ? w1 : word) + (f >> 2) * 14336 + (f >> 1 & 1) * 1024; };
                    uint32_t a[24][4];
                    bar_arrive(B_VP, 384);
                    uint8_t* acc = g_acc + ((s + 1) >> 1) * 32768 + ((s + 1) & 1) * 128 + (u0 + warp) * 1280;
                    uint32_t ln = l16; PIN(ln); ln = ln >> 4 & 31;
                    uint32_t ox = sm + C_OX + ln * 8;
                    uint8_t* a4 = acc + (ln >> 3) * 256 + (ln & 7) * 16; uint8_t* a1 = acc + 1024 + ln * 4;
                    PIN(ox); PINL(a4); PINL(a1);
                    const bool tile = mbar_test(sm + CB_XF, (s + 1) & 1);
#pragma unroll
                    for (int f = 0; f < NW; f++) ldsm4t(a[f], frag(f));
                    if (wg) PROXY_FENCE();
                    float e[2][4];
                    uint32_t ob[12][2];
                    bar_sync(B_OWN, 128 + 32 * nu);
#pragma unroll
                    for (int k = 0; k < 4; k++) lds64(ob[k], ox + k * 256);
#pragma unroll
                    for (int k = 0; k < 4; k++) {
                        SFENCE();
                        if (k > 0) { ldsm4t(a[2 * k - 2 + NW], frag(2 * k - 2 + NW)); ldsm4t(a[2 * k - 1 + NW], frag(2 * k - 1 + NW)); }
                        if (k == 0) { mma16z(e[0], a[0], ob[0][0], ob[0][1]); mma16z(e[1], a[1], ob[0][0], ob[0][1]); }
                        else { mma16(e[0], a[2 * k], ob[k][0], ob[k][1]); mma16(e[1], a[2 * k + 1], ob[k][0], ob[k][1]); }
                    }
                    SFENCE();
                    ldsm4t(a[6 + NW], frag(6 + NW)); ldsm4t(a[7 + NW], frag(7 + NW));
                    PINL(xo); PINL(xt);
                    if (warp == 0) PROF(3);
                    mbar_wait(sm + CB_OX, s & 1);
#pragma unroll
                    for (int k = 4; k < 4 + OD; k++) lds64(ob[k], ox + k * 256);
                    if (warp == 1) PROF(4);
#pragma unroll
                    for (int k = 4; k < 12; k++) {
                        SFENCE();
                        if (k > 4 && k - 1 + OD < 12) lds64(ob[k - 1 + OD], ox + (k - 1 + OD) * 256);
                        if (k > 4 && 2 * k - 2 + NW < 24) { ldsm4t(a[2 * k - 2 + NW], frag(2 * k - 2 + NW)); ldsm4t(a[2 * k - 1 + NW], frag(2 * k - 1 + NW)); }
                        mma16(e[0], a[2 * k], ob[k][0], ob[k][1]); mma16(e[1], a[2 * k + 1], ob[k][0], ob[k][1]);
                    }
                    asm volatile("red.relaxed.gpu.global.add.noftz.v4.f16x2 [%0], {%1,%2,%3,%4};" :: "l"(a4), "r"(packh(e[0][0], e[0][1])), "r"(packh(e[0][2], e[0][3])),
                                 "r"(packh(e[1][0], e[1][1])), "r"(packh(e[1][2], 1.f)) : "memory");
                    asm volatile("red.relaxed.gpu.global.add.noftz.f16x2 [%0], %1;" :: "l"(a1), "r"(packh(e[1][3], 1.f)) : "memory");
                    bar_arrive(B_RED, 384);
                    if (warp == 0) { PROF(5); PROFG(25); }
                    if (!tile) mbar_wait(sm + CB_XF, (s + 1) & 1);
                }
            }
            float acc[16];
#pragma unroll
            for (int i = 0; i < 16; i++) acc[i] = 0.f;
            if (warp == 1) PROF(12);
            WG_FENCE();
#pragma unroll
            for (int n = 0; n < 40; n++) {
                const int i = n < 24 ? n : n < 32 ? n + 4 : n < 36 ? n - 8 : n, ks = pair_idx(i >> 1) * 2 + (i & 1);
                if (n == 32) mbar_wait(sm + CB_XG, (s + 1) & 1);
                wgmma_rs_n32(acc, wa[i], (pair_own(i >> 1) ? xo : xt) + (((ks >> 2) * 4096 + (ks & 3) * 32) >> 4));
                if (n % 4 == 2 && n / 4 < NP) { SFENCE(); ldsm4t(pl[n / 4], wvrd + n / 4 * 2048); }
            }
            WG_COMMIT();
            WG_WAIT(0);
            if (warp == 1) PROF(13);
            bar_sync(B_X, 256);
            uint32_t lx = l16; PIN(lx);
            const uint32_t dst = (lx ^ (lx >> 3 & 48)) + C_QX + wg * 20480 + w * 1024;
            sts128(dst, pack2(acc[0], acc[1]), pack2(acc[4], acc[5]), pack2(acc[8], acc[9]), pack2(acc[12], acc[13]));
            sts128(dst + 512, pack2(acc[2], acc[3]), pack2(acc[6], acc[7]), pack2(acc[10], acc[11]), pack2(acc[14], acc[15]));
            PROXY_FENCE();
            if (warp == 1) PROF(14);
            if (warp == 7) { if (elect()) BULK_WAIT(); __syncwarp(); }
            if (s < 0) {
                PPROF(6);
                mbar_wait(sm + CB_W2, 0);
                PPROF(7);
#pragma unroll
                for (int i = 0; i < NP; i++) ldsm4t(pl[i], wvrd + i * 2048);
            }
            s++;
        }
    } else {
        asm volatile("setmaxnreg.dec.sync.aligned.u32 56;");
        const uint32_t l16 = opaque(sm + lane * 16);
        if (w == 3) {
            const uint64_t ef = policy_stream();
            int c = 0;
#pragma unroll 1
            for (int d = 0; d < 21; d++) {
#pragma unroll 1
                for (; c < 21 && c - d < (d < ar.P[1] ? ar.P[0] : ar.P[2]); c++) {
                    if (c == 10) bar_sync(B_OWN, 160);
                    if (c == 15) bar_sync(B_VM, 160);
                    const uint32_t pb = sm + CB_PC + 8 * (c & 3);
                    if (elect()) {
                        mbar_expect(pb, c < 15 ? 16384 : 14336);
                        if (c < 10) tma2d_ef(sm + C_WV + c * 16384, c < 5 ? &mp.wq : &mp.wk, col0, c % 5 * 128, pb, ef);
                        else if (c < 15) tma2d(sm + C_WV + (c - 10) * 16384, &mp.wv, col0, (c - 10) * 128, pb);
                        else tma3d(sm + C_WO + (c - 15) * 14336, &mp.wo, head * DH + (c - 15 + 2 * j) % 6 * 32, u0, pb);
                    }
                    __syncwarp();
                }
                mbar_wait(sm + CB_PC + 8 * (d & 3), (d >> 2) & 1);
                if ((d == 4 || d == 9 || d == 20) && elect()) mbar_arrive(sm + (d == 4 ? CB_W : d == 9 ? CB_WK : CB_W2));
                __syncwarp();
            }
        } else if (w == 2) {
            if (elect()) {
                flag_add(&g_flags.h);
                PPROF2(12);
                flag_wait(&g_flags.h, 96);
                PPROF2(4);
                h_fetch_a(mp, sm, 0); h_fetch_b(mp, sm, 0);
                flags_release();
                flag_wait(&g_flags.v[head], 2);
                PPROF2(13);
                mbar_expect(sm + CB_VX, 4096);
                bulk_g2s(sm + C_VX, rec0 + j * 4096, 4096, sm + CB_VX);
            }
            __syncwarp();
            if (lane < 16 && blk < 80) g_modt[blk * 16 + lane] = 0;
        }
        uint32_t mx = 0;
#pragma unroll 1
        for (int i = 0; i < 5; i++) { uint32_t v[4]; lds128(v, l16 + C_MEM + (w * 5 + i) * 512); mx = absmax2(absmax2(absmax2(absmax2(mx, v[0]), v[1]), v[2]), v[3]); }
        sts32(sm + C_SCL, 0x3f800000u);
        int ex = 0;
        bool chk = false;
        int nslow = 0;
        uint32_t vb[2][4];
        { const uint32_t vxrd = l16 + lane * 112 + (((2 * w) ^ vswz(lane)) << 4); mbar_wait(sm + CB_VX, 0); ldsm4t(vb[0], vxrd + C_VX); ldsm4t(vb[1], (vxrd ^ 16) + C_VX); }
        bar_sync(B_MEM, 384);
        for (int s = 0; s < NSEG; s++) {
            uint32_t lq = l16; PIN(lq);
            const uint32_t l0 = lq >> 4 & 31, r0 = l0 & 7, m0 = l0 >> 3;
            uint32_t kb[2][4];
            const uint32_t kxrd = sm + C_KX + l0 * 64 + ((w ^ (r0 >> 1)) << 4);
            ldsm4t(kb[0], kxrd); ldsm4t(kb[1], kxrd + 2048);
            if (w == 1 && elect()) BULK_WAIT();
            if (w == 0 && s + 1 < NSEG && elect()) {
                h_fetch_a(mp, sm, s + 1);
                mbar_expect(sm + CB_VX, 4096);
                bulk_g2s(sm + C_VX, rec0 + (size_t)(s + 1) * (NH * REC) + j * 4096, 4096, sm + CB_VX);
            }
            __syncwarp();
            const uint32_t r1 = (1 - 3 * (j >> 1)) << 24, r2 = (2 - 3 * ((j + 1) >> 1)) << 24;
            uint32_t qrd = sm + C_QM + ((m0 >> 1) + 2 * (m0 & 1)) * 128 + r0 * 16, scdst = sm + C_SC + j * 640 + w * 128 + ((l0 * 4) ^ (w * 32)),
                     sc1 = scdst + r1, sc2 = scdst + r2;
            PIN(qrd); PIN(scdst); PIN(sc1); PIN(sc2);
            for (;;) {
                sts32(sm + C_MAX + w * 4, __reduce_max_sync(0xffffffffu, max(mx & 0xffffu, mx >> 16)) >> 7);
                bar_sync(B_AUX, 128);
                uint32_t m4[4]; lds128(m4, sm + C_MAX);
                const int m = __shfl_sync(0xffffffffu, max(max(m4[0], m4[1]), max(m4[2], m4[3])), 0);
                const bool bad = chk && (m == 255 || m < 127 - 6 || ar.force);
                ex = min(max(ex + 130 - m, -40), 40);
                sts32(sm + C_BAD, bad);
                if (!bad) break;
                bar_sync(B_QK, 384);
                bar_sync(B_RED, 384);
                nslow++;
                if (w == 0 && elect()) {
                    asm volatile("red.release.gpu.global.add.u32 [%0], 1;" :: "l"(&g_flags.slow) : "memory");
                    for (int n = 0;; n++) {
                        uint32_t v; asm volatile("ld.acquire.gpu.global.u32 %0, [%1];" : "=r"(v) : "l"(&g_flags.slow) : "memory");
                        if (v >= 96u * nslow) break;
                        if (n > (1 << 23)) __trap();
                    }
                }
                bar_sync(B_AUX, 128);
                mx = 0;
#pragma unroll 1
                for (int i = 0; i < 10; i++) {
                    float4 a = make_float4(0, 0, 0, 0);
#pragma unroll 4
                    for (int h = 0; h < NH; h++) {
                        const float4 v = __ldcg((const float4*)(g_slow + ((((s & 1) * NH + h) * 20 + w * 5 + (i >> 1)) * 32 + l0) * 8) + (i & 1));
                        a.x += v.x; a.y += v.y; a.z += v.z; a.w += v.w;
                    }
                    const uint32_t o0 = pack2(a.x, a.y), o1 = pack2(a.z, a.w);
                    sts32(sm + C_MEM + (w * 10 + i) * 256 + l0 * 4, o0); sts32(sm + C_MEM + (w * 10 + i) * 256 + 128 + l0 * 4, o1);
                    mx = absmax2(absmax2(mx, o0), o1);
                }
                sts32(sm + C_SCL, 0x3f800000u);
                ex = 0; chk = false;
                bar_sync(B_MEM, 384);
            }
            if (s + 1 == NSEG) {
                if (w == 2 && elect()) flag_add(&g_flags.seg[(s - 1) * 32 + head], 2);
                __syncwarp();
                bar_sync(B_QK, 384);
                bar_sync(B_VP, 384);
                const float4 y0 = lds128f(lq + C_VP + w * 512), y1 = lds128f(lq + C_VP + w * 512 + 2048);
                sts32(sm + C_VM + w * 256 + l0 * 4, pack2(y0.x + y1.x, y0.y + y1.y)); sts32(sm + C_VM + w * 256 + 128 + l0 * 4, pack2(y0.z + y1.z, y0.w + y1.w));
                PROXY_FENCE();
                bar_sync(B_RED, 384);
                if (w == 1 && elect()) { bulk_s2g(rec0 + (size_t)s * (NH * REC) + j * R_J + R_KM, sm + C_KM, 2048); BULK_COMMIT(); BULK_WAIT(); flag_add(&g_flags.seg[s * 32 + head]); }
                break;
            }
            if (w == 3) {
                uint32_t qa[2][4], km[2][4], x, y;
                bar_sync(B_QK, 384);
                ldsm4t(qa[0], qrd); ldsm4t(km[0], lq + C_KM); ldsm4t(qa[1], qrd + 512); ldsm4t(km[1], lq + C_KM + 512);
                SFENCE();
                score_tiles(qa, kb, km, x, y);
                stas1(sc1, x, sm + CB_SC + r1); stas1(sc2, x, sm + CB_SC + r2); stas1(sc1 + 128, y, sm + CB_SC + r1); stas1(sc2 + 128, y, sm + CB_SC + r2);
                sts32(scdst, x); sts32(scdst + 128, y);
            } else {
                uint32_t qa[2][4];
                bar_sync(B_QK, 384);
                ldsm4t(qa[0], qrd); ldsm4t(qa[1], qrd + 512);
                if (w == 0) PROF(6);
                const uint32_t x = score_tile(qa, kb);
                stas1(sc1, x, sm + CB_SC + r1); stas1(sc2, x, sm + CB_SC + r2);
                sts32(scdst, x);
            }
            __syncwarp();
            if (elect()) mbar_arrive(sm + CB_SC);
            SFENCE();
            if (w == 0) PROF(7);
            uint32_t scrd = sm + C_SC + (l0 & 3) * 128 + (((l0 >> 2) ^ (2 * (l0 & 3))) << 4), zrd = sm + C_SC + 512 + ((l0 * 4) ^ 96),
                     od = sm + C_OX + l0 * 8 + w * 256, od1 = od + r1 + 2048, od2 = od + r2 + 1024, vprd = lq + C_VP + w * 512, vmst = sm + C_VM + w * 256 + l0 * 4, ones = 0x3f803f80u, ones2 = 0x3f803f80u, zero = 0;
            PIN(scrd); PIN(zrd); PIN(od); PIN(od1); PIN(od2); PIN(vprd); PIN(vmst); PIN(ones); PIN(ones2); PIN(zero);
            mbar_wait(sm + CB_SC, s & 1);
            float sv[10];
            {
                uint32_t x[3][4], z[3];
#pragma unroll
                for (int p = 0; p < 3; p++) { lds128(x[p], scrd + p * 640); z[p] = lds32(zrd + p * 640); }
                if (w == 1) PROF(8);
#pragma unroll
                for (int i = 0; i < 4; i++) { sv[2 * i] = (lo_f(x[0][i]) + lo_f(x[1][i])) + lo_f(x[2][i]); sv[2 * i + 1] = (hi_f(x[0][i]) + hi_f(x[1][i])) + hi_f(x[2][i]); }
                sv[8] = (lo_f(z[0]) + lo_f(z[1])) + lo_f(z[2]); sv[9] = (hi_f(z[0]) + hi_f(z[1])) + hi_f(z[2]);
            }
            float mxs = fmaxf(fmaxf(fmaxf(sv[0], sv[1]), fmaxf(sv[2], sv[3])), fmaxf(fmaxf(fmaxf(sv[4], sv[5]), fmaxf(sv[6], sv[7])), fmaxf(sv[8], sv[9])));
            {
                const float a = __shfl_xor_sync(0xffffffffu, mxs, 1), b = __shfl_xor_sync(0xffffffffu, mxs, 2), c = __shfl_xor_sync(0xffffffffu, mxs, 3);
                mxs = fmaxf(fmaxf(mxs, a), fmaxf(b, c));
            }
#pragma unroll
            for (int i = 0; i < VPB; i++) sv[i] = ex2(sv[i] - mxs);
            SFENCE();
            bar_sync(B_VP, 384);
            const float4 y0 = lds128f(vprd), y1 = lds128f(vprd + 2048);
#pragma unroll
            for (int i = VPB; i < 10; i++) sv[i] = ex2(sv[i] - mxs);
            const uint32_t pa[4] = {pack2(sv[0], sv[1]), pack2(sv[4], sv[5]), pack2(sv[2], sv[3]), pack2(sv[6], sv[7])}, pm = pack2(sv[8], sv[9]);
            if (w == 2) PROF(9);
            {
                float o[2][4], o2[2][4], om[2][4], sx[4], sy[4];
                mma16z(sx, pa, ones, ones2);
                mma16z(o[0], pa, vb[0][0], vb[0][1]); mma16z(o2[0], pa, vb[0][2], vb[0][3]);
                mma8z(sy, pm, zero, ones);
                mma16z(o[1], pa, vb[1][0], vb[1][1]); mma16z(o2[1], pa, vb[1][2], vb[1][3]);
                SFENCE();
                const uint32_t vm0 = pack2(y0.x + y1.x, y0.y + y1.y), vm1 = pack2(y0.z + y1.z, y0.w + y1.w);
                mma8z(om[0], pm, zero, vm0); mma8z(om[1], pm, zero, vm1);
                float inv; asm("rcp.approx.ftz.f32 %0, %1;" : "=f"(inv) : "f"((sx[0] + sx[2]) + sy[0]));
                inv *= __int_as_float((127 + ex) << 23);
                const uint32_t a = pack2(((o[0][0] + o2[0][2]) + om[0][0]) * inv, ((o[0][1] + o2[0][3]) + om[0][1]) * inv),
                               b = pack2(((o[1][0] + o2[1][2]) + om[1][0]) * inv, ((o[1][1] + o2[1][3]) + om[1][1]) * inv);
                stas2(od1, a, b, sm + CB_OX + r1); stas2(od2, a, b, sm + CB_OX + r2);
                asm volatile("st.shared.v2.b32 [%0], {%1,%2};" :: "r"(od), "r"(a), "r"(b) : "memory");
                bar_arrive(B_OWN, 128 + 32 * nu);
                bar_arrive(B_VM, 160);
                sts32(vmst, vm0); sts32(vmst + 128, vm1);
                PROXY_FENCE();
                if (w == 0) PROF(10);
            }
            const uint8_t* acc = g_acc + ((s + 1) >> 1) * 32768 + ((s + 1) & 1) * 128 + w * 1280;
            const uint8_t* a4 = acc + (l0 >> 3) * 256 + (l0 & 7) * 16; const uint8_t* a1 = acc + 1024 + l0 * 4;
            PINL(a4); PINL(a1);
            const uint32_t* vf = &g_flags.v[(min(s + 2, NSEG - 1) >> 2) * 32 + head];
            uint32_t vok = 2;
            if (w == 0 && (s & 3) == 2) vok = ld_rlx(vf);
            if (w == 2 && s > 0 && elect()) flag_add(&g_flags.seg[(s - 1) * 32 + head], 2);
            if (w == 1 && elect()) { mbar_expect(sm + CB_SC, 1280); sts32(sm + C_SCL, (127 - ex) << 23); }
            __syncwarp();
            bar_sync(B_RED, 384);
            SFENCE();
            const uint32_t tw = clock();
            SFENCE();
            if (w == 1 && elect()) {
                mbar_expect(sm + CB_OX, 2048);
                bulk_s2g_ef(rec0 + (size_t)s * (NH * REC) + j * R_J + R_KM, sm + C_KM, 2048, policy_stream()); BULK_COMMIT();
            }
            __syncwarp();
            { const uint32_t vxrd = lq + l0 * 112 + (((2 * w) ^ vswz(l0)) << 4); mbar_wait(sm + CB_VX, (s + 1) & 1); ldsm4t(vb[0], vxrd + C_VX); ldsm4t(vb[1], (vxrd ^ 16) + C_VX); }
            if (__any_sync(0xffffffffu, vok < 2)) flag_wait_warp(vf, 2);
            wait_until(tw + ar.D + (j == 2 ? ar.D2 : 0));
            if (w == 2) PROF(16);
            uint32_t v[5][4], z[5];
            int n = 0;
#pragma unroll
            for (int i = 0; i < 5; i++) {
                asm volatile("ld.relaxed.gpu.global.v4.u32 {%0,%1,%2,%3}, [%4];" : "=r"(v[i][0]), "=r"(v[i][1]), "=r"(v[i][2]), "=r"(v[i][3]) : "l"(a4 + (4 - i) * 5120) : "memory");
                asm volatile("ld.relaxed.gpu.global.u32 %0, [%1];" : "=r"(z[i]) : "l"(a1 + (4 - i) * 5120) : "memory");
            }
            if (w == 1 && elect()) BULK_WAIT_READ();
            __syncwarp();
            while (__any_sync(0xffffffffu, min(min(min(v[0][3], z[0]), min(v[1][3], z[1])), min(min(min(v[2][3], z[2]), min(v[3][3], z[3])), min(v[4][3], z[4]))) < 0x50000000u)) {
#pragma unroll
                for (int i = 0; i < 5; i++) {
                    asm volatile("{ .reg .pred q; setp.lt.u32 q, %3, 0x50000000;\n@q ld.relaxed.gpu.global.v4.u32 {%0,%1,%2,%3}, [%4]; }" : "+r"(v[i][0]), "+r"(v[i][1]), "+r"(v[i][2]), "+r"(v[i][3]) : "l"(a4 + (4 - i) * 5120) : "memory");
                    asm volatile("{ .reg .pred q; setp.lt.u32 q, %0, 0x50000000;\n@q ld.relaxed.gpu.global.u32 %0, [%1]; }" : "+r"(z[i]) : "l"(a1 + (4 - i) * 5120) : "memory");
                }
                if (++n > SPIN_LIMIT) __trap();
            }
            if (w == 0) { PROF(11); PROFV(15, n); }
#pragma unroll
            for (int i = 0; i < 5; i++) {
                v[i][0] = h2b(v[i][0]); v[i][1] = h2b(v[i][1]); v[i][2] = h2b(v[i][2]); v[i][3] = h2b_lo(v[i][3], z[i]);
                stsm4(lq + C_MEM + w * 512 + (4 - i) * 2048, v[i][0], v[i][1], v[i][2], v[i][3]);
            }
            bar_sync(B_MEM, 384);
            SFENCE();
            mx = 0;
#pragma unroll
            for (int i = 0; i < 5; i++) mx = absmax2(absmax2(absmax2(absmax2(mx, v[i][0]), v[i][1]), v[i][2]), v[i][3]);
            chk = true;
        }
    }
}

struct SideMaps { CUtensorMap h, wv, ost, o, o64, wo, slab3, slab2, ln[3], wgate, wup, wdown; };
constexpr int NRUN = 48;
struct Sched { uint16_t end[NRUN + 1]; uint8_t kind[NRUN + 1], block[NRUN + 1], lsplit[16], slab[16]; int bgrows; };
constexpr int SD_SL = REC / 3, SD_NSL = 12, SD_EPI = SD_NSL * SD_SL, SD_VEC = SD_EPI + 2 * 24576, SD_BAR = SD_VEC + 6400, SD_SMEM = SD_BAR + 768;
static_assert(SD_SMEM <= 232448, "side shared memory");

template <int NPC, bool V>
__device__ __forceinline__ void tile_out(const float (&acc)[8 * NPC], uint32_t eb, uint32_t efull, uint32_t eempty, int& eph, int w, int lane) {
    const int r = lane & 7, mi = lane >> 3, row = w * 16 + (mi & 1) * 8 + r;
    const uint32_t rb = V ? eb + (row >> 5) * 12288 + (row & 31) * 128 : eb + row * 128, sw = V ? vswz(row & 31) : r;
    mbar_wait(eempty, eph); eph ^= 1;
#pragma unroll
    for (int p = 0; p < NPC; p++) {
        const int oc = 2 * p + (mi >> 1);
        stsm4(rb + (oc >> 3) * (V ? 4096 : 8192) + (((oc & 7) ^ sw) << 4), pack2(acc[8 * p], acc[8 * p + 1]), pack2(acc[8 * p + 2], acc[8 * p + 3]),
              pack2(acc[8 * p + 4], acc[8 * p + 5]), pack2(acc[8 * p + 6], acc[8 * p + 7]));
    }
    PROXY_FENCE();
    __syncwarp();
    if (lane == 0) mbar_arrive(efull);
}

__device__ __forceinline__ void arrive_after(uint32_t bar, uint32_t zero, uint32_t a, uint32_t b, uint32_t c, uint32_t d, int lane) {
    if (lane == 0) mbar_arrive(bar + ((a | b | c | d) & zero));
}
__device__ __forceinline__ uint32_t bmax(uint32_t a, uint32_t b) { uint32_t r; asm("max.bf16x2 %0, %1, %2;" : "=r"(r) : "r"(a), "r"(b)); return r; }
__device__ __forceinline__ void attn_units(uint32_t base, uint32_t dst, uint32_t bars, int mt, int lane) {
    const uint32_t FQ = bars, FV = bars + 8, EQ = bars + 16, PD = bars + 24, SE = bars + 32, EV = bars + 40, STOP = bars + 48;
    const int r = lane & 7, mi = lane >> 3, g = lane >> 2, t = lane & 3;
    const uint32_t tok = 8 * (r >> 1) + 2 * mi + (r & 1);
    const uint32_t qrd = opaque(base + R_Q + ((mi >> 1) * 8 + r) * 64 + (((2 * mt + (mi & 1)) ^ (r >> 1)) << 4)), mrd = opaque(base + lane * 16), zero = opaque(lane >> 5);
    uint32_t krd[4], vrd[8], ost[4], vis[2][4];
#pragma unroll
    for (int n = 0; n < 4; n++) {
        krd[n] = opaque(base + R_K + lane * 64 + ((n ^ (r >> 1)) << 4));
        ost[n] = opaque(dst + ((mi & 1) * 8 + r) * 128 + (((2 * n + (mi >> 1)) ^ r) << 4));
#pragma unroll
        for (int hf = 0; hf < 2; hf++) {
            const int lim = 8 * (g >> 1) + 2 * (2 * mt + hf) + (g & 1) - 8 * t - 2 * n;
            vis[hf][n] = opaque(lim < 0 ? 0u : lim < 1 ? 0xffffu : ~0u);
        }
    }
#pragma unroll
    for (int u = 0; u < 8; u++) vrd[u] = opaque(base + tok * 128 + ((u ^ vswz(tok)) << 4));
    const float scale = 0.07216878364870322f, l2e = 1.4426950408889634f;
#pragma unroll 1
    for (int ph = 0;; ph ^= 1) {
        mbar_wait(FQ, ph);
        float sc[5][4];
        uint32_t a[6][2][4], bb[6][5][4], bm[6][4];
        auto load = [&](int k2) {
            const uint32_t cb = (k2 >> 1) * R_J + (k2 & 1) * 2048;
            ldsm4t(a[k2][0], qrd + cb);
#pragma unroll
            for (int n = 0; n < 4; n++) ldsm4t(bb[k2][n], krd[n] + cb);
            ldsm4t(bb[k2][4], mrd + R_KM + (k2 >> 1) * R_J + (k2 & 1) * 512);
            ldsm4t(a[k2][1], qrd + cb + 1024);
        };
        const uint32_t stop = lds32(STOP);
        load(0); load(1);
        if (stop) break;
#pragma unroll
        for (int k2 = 0; k2 < 6; k2++) {
            SFENCE();
            if (k2 + 2 < 6) load(k2 + 2);
            else {
#pragma unroll
                for (int n = 0; n < 3; n++) { const int n4 = 3 * (k2 - 4) + n; ldsm4(bm[n4], mrd + R_VM + (n4 >> 1) * R_J + (n4 & 1) * 512); }
            }
#pragma unroll
            for (int n = 0; n < 5; n++) { if (k2 == 0) mma16z(sc[n], a[k2][0], bb[k2][n][0], bb[k2][n][1]); else mma16(sc[n], a[k2][0], bb[k2][n][0], bb[k2][n][1]); }
#pragma unroll
            for (int n = 0; n < 5; n++) mma16(sc[n], a[k2][1], bb[k2][n][2], bb[k2][n][3]);
        }
        uint32_t vb[6][4][4];
        auto vload = [&](int n4) {
#pragma unroll
            for (int u = 0; u < 4; u++) ldsm4t(vb[n4][u], vrd[(n4 & 1) * 4 + u] + (n4 >> 1) * 4096);
        };
        uint32_t sv[2][5], mx[2];
#pragma unroll
        for (int hf = 0; hf < 2; hf++) {
#pragma unroll
            for (int n = 0; n < 5; n++) {
                uint32_t u = pack2(sc[n][2 * hf], sc[n][2 * hf + 1]);
                u = pack2(lo_f(u) * scale, hi_f(u) * scale);
                sv[hf][n] = n < 4 ? (u & vis[hf][n & 3]) | (0xce6ece6eu & ~vis[hf][n & 3]) : u;
            }
            mx[hf] = bmax(bmax(bmax(sv[hf][0], sv[hf][1]), bmax(sv[hf][2], sv[hf][3])), sv[hf][4]);
        }
        arrive_after(EQ, zero, bm[0][0] | bm[1][0], bm[2][0] | bm[3][0], bm[4][0], bm[5][0], lane);
        uint32_t m2 = bmax(__byte_perm(mx[0], mx[1], 0x5410), __byte_perm(mx[0], mx[1], 0x7632));
        m2 = bmax(bmax(m2, __shfl_xor_sync(0xffffffffu, m2, 1)), bmax(__shfl_xor_sync(0xffffffffu, m2, 2), __shfl_xor_sync(0xffffffffu, m2, 3)));
        float v[2][10], sum[2];
#pragma unroll
        for (int hf = 0; hf < 2; hf++) {
            const float m = hf ? hi_f(m2) : lo_f(m2);
#pragma unroll
            for (int q = 0; q < 10; q++) asm("ex2.approx.ftz.f32 %0, %1;" : "=f"(v[hf][q]) : "f"(((q & 1 ? hi_f(sv[hf][q >> 1]) : lo_f(sv[hf][q >> 1])) - m) * l2e));
            sum[hf] = (((v[hf][0] + v[hf][1]) + (v[hf][2] + v[hf][3])) + ((v[hf][4] + v[hf][5]) + (v[hf][6] + v[hf][7]))) + (v[hf][8] + v[hf][9]);
        }
#pragma unroll
        for (int o = 1; o < 4; o <<= 1)
#pragma unroll
            for (int hf = 0; hf < 2; hf++) sum[hf] += __shfl_xor_sync(0xffffffffu, sum[hf], o);
        mbar_wait(FV, ph);
        vload(0); vload(1); vload(2); vload(3);
        SFENCE();
        uint32_t pa[2][4], pm[2];
#pragma unroll
        for (int hf = 0; hf < 2; hf++) {
            float inv; asm("rcp.approx.ftz.f32 %0, %1;" : "=f"(inv) : "f"(sum[hf]));
#pragma unroll
            for (int n = 0; n < 4; n++) pa[n >> 1][2 * (n & 1) + hf] = pack2(v[hf][2 * n] * inv, v[hf][2 * n + 1] * inv);
            pm[hf] = pack2(v[hf][8] * inv, v[hf][9] * inv);
        }
        mbar_wait(SE, ph ^ 1);
        float o[6][4][4];
#pragma unroll
        for (int n4 = 0; n4 < 7; n4++) {
            SFENCE();
            if (n4 == 1 || n4 == 2) vload(n4 + 3);
            if (n4 == 4) arrive_after(EV, zero, vb[4][0][0] | vb[5][0][0], vb[4][1][0] | vb[5][1][0], vb[4][2][0] | vb[5][2][0], vb[4][3][0] | vb[5][3][0], lane);
            if (n4 < 6) {
#pragma unroll
                for (int u = 0; u < 4; u++) mma8z(o[n4][u], pm[0], pm[1], bm[n4][u]);
#pragma unroll
                for (int h = 0; h < 2; h++)
#pragma unroll
                    for (int u = 0; u < 4; u++) mma16(o[n4][u], pa[h], vb[n4][u][2 * h], vb[n4][u][2 * h + 1]);
            }
            if (n4 > 0) {
#pragma unroll
                for (int p = 0; p < 2; p++) {
                    const float (&x)[4] = o[n4 - 1][2 * p], (&y)[4] = o[n4 - 1][2 * p + 1];
                    stsm4(ost[((n4 - 1) & 1) * 2 + p] + ((n4 - 1) >> 1) * 4096, pack2(x[0], x[1]), pack2(x[2], x[3]), pack2(y[0], y[1]), pack2(y[2], y[3]));
                }
            }
        }
        PROXY_FENCE();
        __syncwarp();
        if (lane == 0) mbar_arrive(PD);
    }
}

__device__ __forceinline__ void ln2_row(const uint32_t (&av)[5][2], const uint2 (&xn)[5], int row, uint32_t vec, bf16* out, uint64_t ef, int lane) {
    uint32_t xv[10], hv[10];
#pragma unroll
    for (int q2 = 0; q2 < 5; q2++) {
        uint32_t ga[2]; lds64(ga, vec + q2 * 256);
        xv[2 * q2] = badd(xn[q2].x, bmul(ga[0], av[q2][0]));
        xv[2 * q2 + 1] = badd(xn[q2].y, bmul(ga[1], av[q2][1]));
    }
    ln_row(xv, hv);
    float r0 = 0, r1 = 0;
#pragma unroll
    for (int q2 = 0; q2 < 5; q2++) {
        const int c = row * DM + lane * 4 + q2 * 128;
        uint32_t sh[2], sc[2], gb[2], wv[2];
        lds64(sh, vec + 1280 + q2 * 256); lds64(sc, vec + 2560 + q2 * 256); lds64(gb, vec + 3840 + q2 * 256); lds64(wv, vec + 5120 + q2 * 256);
        const uint32_t h0 = badd(bmul(hv[2 * q2], badd(sc[0], 0x3f803f80u)), sh[0]), h1 = badd(bmul(hv[2 * q2 + 1], badd(sc[1], 0x3f803f80u)), sh[1]);
        r0 += lo_f(h0) * lo_f(wv[0]) + hi_f(h0) * hi_f(wv[0]); r1 += lo_f(h1) * lo_f(wv[1]) + hi_f(h1) * hi_f(wv[1]);
        st_ef(g_h2 + c, make_uint2(h0, h1), ef);
        st_ef(g_x1 + c, make_uint2(xv[2 * q2], xv[2 * q2 + 1]), ef);
        st_ef(out + c, make_uint2(badd(xv[2 * q2], bmul(gb[0], h0)), badd(xv[2 * q2 + 1], bmul(gb[1], h1))), ef);
    }
    const float rsum = warp_sum(r0 + r1);
    if (lane == 0) g_r[row] = __float2bfloat16_rn(rsum);
}
__device__ __forceinline__ int pos_row(int pos) { return (pos & ~31) + 8 * ((pos & 7) >> 1) + 2 * ((pos >> 3) & 3) + (pos & 1); }
__device__ __forceinline__ uint32_t claim(uint32_t* ctr) {
    uint32_t v; asm volatile("{ .reg .pred e; elect.sync _|e, -1; mov.u32 %0, 0; @e atom.relaxed.gpu.global.add.u32 %0, [%1], 1; }" : "=r"(v) : "l"(ctr) : "memory"); return v;
}
__device__ __forceinline__ void flag_wait_idle(const uint32_t* f, uint32_t target) {
    for (int n = 0; !__all_sync(0xffffffffu, ld_rlx(f) >= target); n++) { __nanosleep(400); if (n > (1 << 20)) __trap(); }
}
#define APROF(u)
__device__ __forceinline__ void attn_manager(const SideMaps& mp, uint32_t base, uint32_t stg, uint32_t bars, int& ph, const bf16* x, uint64_t ef) {
    const uint32_t FQ = bars, FV = bars + 8, EQ = bars + 16, PD = bars + 24, SE = bars + 32, EV = bars + 40, STOP = bars + 48;
    int prev = -1, pend = -1;
    auto flush = [&]() {
        if (pend >= 0 && elect()) { BULK_WAIT_READ(); mbar_arrive(SE); BULK_WAIT(); flag_add(&g_flags.at[(pend >> 6) * 32 + (pend & 31)]); APROF(pend); }
        pend = -1; __syncwarp();
    };
    auto store = [&]() {
        mbar_wait(PD, ph ^ 1);
        if (elect()) { tma3d_store(&mp.ost, prev & ~31, (prev & 31) * 3, stg, ef, false); BULK_COMMIT(); }
        pend = prev; prev = -1;
    };
    int u = __reduce_max_sync(0xffffffffu, claim(&g_flags.anext));
    uint32_t fl = 0;
#pragma unroll 1
    for (;;) {
        if (u >= NSEG * NH || !__all_sync(0xffffffffu, fl >= 6)) {
            flush();
            if (u < NSEG * NH && __all_sync(0xffffffffu, ld_rlx(&g_flags.seg[u]) >= 6)) {}
            else {
                if (prev >= 0) { store(); flush(); }
                if (u >= NSEG * NH) break;
                flag_wait_warp(&g_flags.seg[u], 6);
            }
        }
        const uint8_t* rec = g_rec + (size_t)u * REC;
        const uint32_t nxt = claim(&g_flags.anext);
        mbar_wait(EQ, ph ^ 1);
        if (elect()) { mbar_expect(FQ, REC - R_Q); bulk_g2s_ef(base + R_Q, rec + R_Q, REC - R_Q, FQ, ef); }
        const int un = __reduce_max_sync(0xffffffffu, nxt);
        fl = ld_rlx(&g_flags.seg[min(un, NSEG * NH - 1)]);
        flush();
        mbar_wait(EV, ph ^ 1);
        if (elect()) {
            mbar_expect(FV, R_Q); bulk_g2s_ef(base, rec, R_Q, FV, ef);
            asm volatile("cp.async.bulk.prefetch.L2.global [%0], 1280;" :: "l"(x + u * DM) : "memory");
        }
        if (prev >= 0) store();
        prev = u; ph ^= 1; u = un;
    }
    if (elect()) { sts32(STOP, 1); mbar_arrive(FQ); }
    __syncwarp();
}

#define SPROF(tk, i)
#define FWAIT(bar, par) mbar_wait(bar, par)
#define EPROF()
#define TPROF(i)
__device__ __forceinline__ void side_tail(uint32_t wgu, uint32_t wgu_bar, int wgu_ph, uint32_t wd, uint32_t wd_bar, int wd_ph, uint32_t xb, uint32_t gbar, bf16* out, int tid) {
    const int warp = __shfl_sync(0xffffffffu, tid >> 5, 0), lane = tid & 31, r = lane & 7, mi = lane >> 3, blk = blockIdx.x;
    const uint32_t T_GU = xb, T_X = xb + 24576, T_RED = T_X + 10240, T_KEY = T_RED + 8192;
    TPROF(0);
    auto rkey = [](int idx) { uint32_t u = __ldcg((const unsigned short*)g_r + idx); u = (u & 0x8000u) ? (~u & 0xffffu) : (u | 0x8000u); return (u << 16) | (uint32_t)(S_TOK - 1 - idx); };
    {
        if (warp == 0 && lane < 15) flag_wait(&g_flags.ln[lane * 32], 128);
        bar_sync(1, 256);
        uint32_t k[8];
#pragma unroll
        for (int i = 0; i < 8; i++) { const int idx = warp * 240 + i * 32 + lane; k[i] = i * 32 + lane < 240 ? rkey(idx) : 0u; }
#pragma unroll 1
        for (int it = 0; it < 8; it++) {
            const uint32_t m = __reduce_max_sync(0xffffffffu, max(umax3(k[0], k[1], k[2]), max(umax3(k[3], k[4], k[5]), max(k[6], k[7]))));
#pragma unroll
            for (int i = 0; i < 8; i++) if (k[i] == m) k[i] = 0;
            if (lane == 0) sts32(T_KEY + (warp * 8 + it) * 4, m);
        }
    }
    bar_sync(1, 256);
    if (warp == 0) {
        uint32_t k[6];
        k[0] = lds32(T_KEY + lane * 4); k[1] = lds32(T_KEY + 128 + lane * 4);
        if (lane == 0) flag_wait(&g_flags.ln[15 * 32], 128);
        __syncwarp();
        TPROF(1);
#pragma unroll
        for (int i = 0; i < 4; i++) k[2 + i] = rkey(1920 + i * 32 + lane);
#pragma unroll 1
        for (int it = 0; it < 8; it++) {
            const uint32_t m = __reduce_max_sync(0xffffffffu, max(umax3(k[0], k[1], k[2]), umax3(k[3], k[4], k[5])));
#pragma unroll
            for (int i = 0; i < 6; i++) if (k[i] == m) k[i] = 0;
            if (lane == 0) sts32(T_KEY + 256 + it * 4, S_TOK - 1 - (m & 0xffffu));
        }
    }
    bar_sync(1, 256);
    TPROF(2);
    {
        const bf16* src = g_h2 + lds32(T_KEY + 256 + (tid & 7) * 4) * DM + (tid >> 3) * 8;
        uint4 v[3];
#pragma unroll
        for (int i = 0; i < 3; i++) if (i < 2 || tid < 128) v[i] = __ldcg((const uint4*)(src + i * 256));
#pragma unroll
        for (int i = 0; i < 3; i++) if (i < 2 || tid < 128) sts128(T_X + tid * 16 + i * 4096, v[i].x, v[i].y, v[i].z, v[i].w);
    }
    const int trow = lds32(T_KEY + 256 + (lane >> 2) * 4), tcol = (blk < 80 ? blk : 0) * 8 + (lane & 3) * 2;
    const uint32_t fx1 = __ldcg((const uint32_t*)(g_x1 + trow * DM + tcol)), fh2 = __ldcg((const uint32_t*)(g_h2 + trow * DM + tcol)),
                   fgb = __ldcg((const uint32_t*)(g_mod + 5 * DM + tcol));
    const float fr = __uint_as_float((uint32_t)__ldcg((const unsigned short*)g_r + trow) << 16);
    mbar_wait(wgu_bar, wgu_ph);
    bar_sync(1, 256);
    TPROF(3);
    {
        float dg[4] = {0, 0, 0, 0}, du[4] = {0, 0, 0, 0};
#pragma unroll
        for (int k = 0; k < 5; k++) {
            uint32_t b[4], ag[4], au[4];
            ldsm4(b, T_X + (warp * 5 + k) * 256 + (lane & 15) * 16);
            const uint32_t o = ((warp * 5 + k) * 16 + (mi >> 1) * 8 + r) * 32 + (mi & 1) * 16;
            ldsm4t(ag, wgu + o); ldsm4t(au, wgu + 20480 + o);
            mma16(dg, ag, b[0], b[1]); mma16(du, au, b[0], b[1]);
        }
        sts128f(T_RED + warp * 1024 + lane * 16, dg[0], dg[1], dg[2], dg[3]); sts128f(T_RED + warp * 1024 + 512 + lane * 16, du[0], du[1], du[2], du[3]);
    }
    bar_sync(1, 256);
    if (warp == 0) {
        float g4[4] = {0, 0, 0, 0}, u4[4] = {0, 0, 0, 0};
#pragma unroll
        for (int i = 0; i < 8; i++) {
            const float4 a = lds128f(T_RED + i * 1024 + lane * 16), b = lds128f(T_RED + i * 1024 + 512 + lane * 16);
            g4[0] += a.x; g4[1] += a.y; g4[2] += a.z; g4[3] += a.w; u4[0] += b.x; u4[1] += b.y; u4[2] += b.z; u4[3] += b.w;
        }
        float y[4];
#pragma unroll
        for (int i = 0; i < 4; i++) { const float gq = bfr(g4[i]); y[i] = bfr(__fdividef(gq, 1.f + __expf(-gq))) * bfr(u4[i]); }
        g_gu[blk * 64 + lane] = movm_t(pack2(y[0], y[1])); g_gu[blk * 64 + 32 + lane] = movm_t(pack2(y[2], y[3]));
        __syncwarp();
        TPROF(4);
        if (lane == 0) {
            flag_add(&g_flags.gu);
            if (blk < 80) {
                flag_wait(&g_flags.gu, 96);
                mbar_expect(gbar, 24576); bulk_g2s(T_GU, g_gu, 24576, gbar);
            }
        }
        __syncwarp();
    }
    if (blk < 80) {
        mbar_wait(wd_bar, wd_ph);
        mbar_wait(gbar, 0);
        TPROF(5);
        float d[2][4] = {{0, 0, 0, 0}, {0, 0, 0, 0}};
#pragma unroll
        for (int k2 = 0; k2 < 6; k2++) {
            uint32_t b[4]; ldsm4t(b, wd + (warp * 6 + k2) * 512 + lane * 16);
#pragma unroll
            for (int h = 0; h < 2; h++) {
                uint32_t a[4]; ldsm4(a, T_GU + ((warp * 12 + k2 * 2 + h) * 2 + (mi >> 1)) * 128 + r * 16);
                mma16(d[h], a, b[2 * h], b[2 * h + 1]);
            }
        }
        asm volatile("st.shared.v2.f32 [%0], {%1,%2};" :: "r"(T_X + warp * 256 + lane * 8), "f"(d[0][0] + d[1][0]), "f"(d[0][1] + d[1][1]) : "memory");
        bar_sync(1, 256);
        if (warp == 0) {
            float y0 = 0, y1 = 0;
#pragma unroll
            for (int i = 0; i < 8; i++) { const float2 a = lds64f(T_X + i * 256 + lane * 8); y0 += a.x; y1 += a.y; }
            const float sg = bfr(__fdividef(1.f, 1.f + __expf(-fr)));
            const float b0 = bfr(lo_f(fh2) + bfr(bfr(y0) * sg)), b1 = bfr(hi_f(fh2) + bfr(bfr(y1) * sg));
            *(uint32_t*)(out + trow * DM + tcol) = pack2(lo_f(fx1) + bfr(lo_f(fgb) * b0), hi_f(fx1) + bfr(hi_f(fgb) * b1));
        }
    }
    TPROF(6);
}

__global__ void __launch_bounds__(512, 1) k_side(const __grid_constant__ SideMaps mp, const __grid_constant__ Sched sd, const bf16* __restrict__ x,
                                                 const bf16* __restrict__ wr, const bf16* __restrict__ cin, const bf16* __restrict__ wmod, bf16* __restrict__ out) {
    extern __shared__ __align__(1024) uint8_t smraw[];
    const uint32_t sm = smem_u32(smraw);
    if (sm & 1023) __trap();
    const uint32_t FULL = sm + SD_BAR, EMPTY = FULL + 96, EFULL = FULL + 192, EEMPTY = EFULL + 16, IFULL = EFULL + 32, IEMPTY = EFULL + 64, IQ = EFULL + 96,
                   VEC = EFULL + 112, GBAR = EFULL + 120, LNDONE = EFULL + 128, LNFREE = EFULL + 136, GO = EFULL + 144, ATT = FULL + 512;
    const int tid = threadIdx.x, warp = __shfl_sync(0xffffffffu, tid >> 5, 0), lane = tid & 31;
    const uint64_t ef = policy_stream();
    if (tid >= 32 && tid < 32 + SD_NSL) { mbar_init(FULL + 8 * (tid - 32), 1); mbar_init(EMPTY + 8 * (tid - 32), 8); asm volatile("fence.mbarrier_init.release.cluster;" ::: "memory"); }
    if (tid >= 64 && tid < 96) {
        const int k = tid & 7;
        if (k < 6) mbar_init(ATT + (tid - 64) * 8, k == 2 || k == 3 || k == 5 ? 2 : 1); else sts32(ATT + (tid - 64) * 8, 0);
        asm volatile("fence.mbarrier_init.release.cluster;" ::: "memory");
    }
    if (tid == 0) {
        mbar_init(GO, 1);
        for (int i = 0; i < 2; i++) { mbar_init(EFULL + 8 * i, 4); mbar_init(EEMPTY + 8 * i, 1); }
        for (int i = 0; i < 4; i++) { mbar_init(IFULL + 8 * i, 1); mbar_init(IEMPTY + 8 * i, 11); }
        mbar_init(VEC, 1); mbar_init(GBAR, 1); mbar_init(LNDONE, 8); mbar_init(LNFREE, 1);
        asm volatile("fence.mbarrier_init.release.cluster;" ::: "memory");
    }
    __syncthreads();
    if (warp >= 12) {
        asm volatile("setmaxnreg.dec.sync.aligned.u32 72;");
        mbar_wait(GO, 0);
        bool vec = false;
#pragma unroll 1
        for (;;) {
            const int t = __reduce_max_sync(0xffffffffu, claim(&g_flags.bnext));
            if (t < 40) {
                flag_wait_idle(&g_flags.v[0], 2);
                float a0 = 0, a1 = 0;
                const uint32_t* src = (const uint32_t*)(wmod + 2 * DM + t * 64) + lane;
#pragma unroll 1
                for (int k0 = 0; k0 < DM; k0 += 64) {
                    const uint32_t cv = silu2(__ldg((const uint32_t*)cin + k0 / 2 + lane));
#pragma unroll 1
                    for (int k1 = 0; k1 < 64; k1 += 32) {
                        uint32_t wv[32];
#pragma unroll
                        for (int k = 0; k < 32; k++) wv[k] = __ldcs(src + (size_t)(k0 + k1 + k) * (3 * DM));
#pragma unroll
                        for (int k = 0; k < 32; k += 2) {
                            const uint32_t c2 = __shfl_sync(0xffffffffu, cv, (k1 + k) >> 1);
                            a0 += lo_f(c2) * lo_f(wv[k]) + hi_f(c2) * lo_f(wv[k + 1]); a1 += lo_f(c2) * hi_f(wv[k]) + hi_f(c2) * hi_f(wv[k + 1]);
                        }
                    }
                }
                ((uint32_t*)(g_mod + 2 * DM + t * 64))[lane] = pack2(a0, a1);
                __syncwarp();
                if (lane == 0) flag_add(&g_flags.mod);
                continue;
            }
            if (!vec) {
                vec = true;
                if (warp == 12) {
                    flag_wait_idle(&g_flags.mod, 40);
                    if (elect()) { mbar_expect(VEC, 6400); bulk_g2s(sm + SD_VEC, g_mod + 2 * DM, 5120, VEC); bulk_g2s(sm + SD_VEC + 5120, wr, 1280, VEC); }
                    __syncwarp();
                    mbar_wait(VEC, 0);
                }
            }
            const int pos = t - 40, b = pos >> 7;
            if (pos >= sd.bgrows) break;
            const int ls = sd.lsplit[b], row = pos_row(pos);
            flag_wait_idle(&g_flags.o[(pos >> 6) * 32], 4u << ls);
            float av[20];
#pragma unroll
            for (int n = 0; n < 20; n++) av[n] = 0.f;
            const bf16* sl = g_slab + ((size_t)sd.slab[b] * 128 + (pos & 127)) * DM + lane * 4;
#pragma unroll 1
            for (int k = 0; k < (1 << ls); k += 2) {
                uint2 z[2][5];
#pragma unroll
                for (int n = 0; n < 10; n++) z[n / 5][n % 5] = ld_ef(sl + (size_t)(k + n / 5) * (128 * DM) + n % 5 * 128, ef);
#pragma unroll
                for (int n = 0; n < 10; n++) { const uint2 v = z[n / 5][n % 5]; float* a = av + 4 * (n % 5); a[0] += lo_f(v.x); a[1] += hi_f(v.x); a[2] += lo_f(v.y); a[3] += hi_f(v.y); }
            }
            uint2 xn[5];
#pragma unroll
            for (int q2 = 0; q2 < 5; q2++) xn[q2] = ld_ef(x + row * DM + lane * 4 + q2 * 128, ef);
            uint32_t ap[5][2];
#pragma unroll
            for (int n = 0; n < 10; n++) ap[n >> 1][n & 1] = pack2(av[2 * n], av[2 * n + 1]);
            mbar_wait(VEC, 0);
            ln2_row(ap, xn, row, sm + SD_VEC + lane * 8, out, ef, lane);
            __syncwarp();
            if (lane == 0) flag_add(&g_flags.ln[b * 32]);
        }
    } else if (warp >= 8) {
      asm volatile("setmaxnreg.dec.sync.aligned.u32 40;");
      int aph = 0; bool att = false;
      auto manage = [&]() {
          bar_sync(2, 384);
          attn_manager(mp, sm + (warp - 8) * REC, sm + SD_EPI + (warp - 8) * 12288, ATT + (warp - 8) * 64, aph, x, ef);
          bar_sync(2, 384);
      };
      if (warp == 8) {
        uint32_t nxt = claim(&g_flags.next);
        int st = 0, ph = 1, run = 0;
        auto take = [&](int n, int bytes) {
            mbar_wait(EMPTY + 8 * (st + n - 1), ph);
            asm volatile("{ .reg .pred p; setp.lt.u32 p, %2, %3; @p mbarrier.arrive.expect_tx.shared::cta.b64 _, [%0], %1; }"
                :: "r"(FULL + 8 * (st + lane)), "r"(lane ? 0 : bytes), "r"(lane), "r"(n) : "memory");
        };
        auto step = [&](int n) { st += n; if (st == SD_NSL) { st = 0; ph ^= 1; } };
#pragma unroll 1
        for (int q = 0;; q++) {
            const int tk = __reduce_max_sync(0xffffffffu, nxt);
            while (tk >= sd.end[run]) run++;
            const int kind = sd.kind[run], b = sd.block[run], i = tk - (run ? sd.end[run - 1] : 0), ls = sd.lsplit[b];
            mbar_wait(IEMPTY + 8 * (q & 3), ((q >> 2) & 1) ^ 1);
            if (elect()) {
                sts32(IQ + 4 * (q & 3), kind << 12 | b << 8 | (i & 255));
                mbar_arrive(IFULL + 8 * (q & 3));
            }
            __syncwarp();
            const int pad = kind == 2 || kind > 4 ? st & 1 : (12 - st) % 3;
            if (pad) { take(pad, 0); step(pad); }
            int kb0 = 0;
            if (q == 0) {
                if (kind == 0) {
#pragma unroll 1
                    for (; kb0 < 4; kb0++) { take(3, 40960); if (elect()) tma3d(sm + st * SD_SL + 16384, &mp.wv, kb0 * 64, i * 3, FULL + 8 * st); step(3); }
                }
                flag_wait_warp(&g_flags.h, 96);
                if (elect()) mbar_arrive(GO);
#pragma unroll 1
                for (int kb = 0; kb < kb0; kb++) if (elect()) tma2d(sm + kb * 3 * SD_SL, &mp.h, kb * 64, b * 128, FULL + 24 * kb);
            }
            if (kind == 0) {
#pragma unroll 1
                for (int kb = kb0; kb < 10; kb++) {
                    take(3, 40960);
                    if (elect()) { tma2d(sm + st * SD_SL, &mp.h, kb * 64, b * 128, FULL + 8 * st); tma3d(sm + st * SD_SL + 16384, &mp.wv, kb * 64, i * 3, FULL + 8 * st); }
                    if (kb == 8) nxt = claim(&g_flags.next);
                    step(3);
                }
            } else if (kind == 1) {
                if (!att) manage();
                att = true;
                nxt = claim(&g_flags.next);
            } else if (kind == 2 || kind > 4) {
                const int nst = 192 >> ls, kf = (i >> 1) * nst * 32, row = b * 128 + (kind == 6 ? 64 : 0), bytes = kind == 2 ? 28672 : 24576;
                const CUtensorMap* om = kind == 2 ? &mp.o : &mp.o64;
                const uint32_t* af = &g_flags.at[(2 * b + (kind == 2 ? lane >> 4 : kind - 5)) * 32 + (i >> 1) * (32 >> ls) + (lane & ((32 >> ls) - 1))];
                int kb = 0;
                if (!__all_sync(0xffffffffu, ld_rlx(af) >= 2)) {
#pragma unroll 1
                    for (; kb < 6; kb++) { take(2, bytes); if (elect()) tma3d(sm + st * SD_SL + 8192, &mp.wo, kf + kb * 32, (i & 1) * 5, FULL + 8 * st); step(2); }
                    flag_wait_warp(af, 2);
#pragma unroll 1
                    for (int n = 0; n < 6; n++) { const int sl = (st + 2 * n) % SD_NSL; if (elect()) tma2d(sm + sl * SD_SL, om, kf + n * 32, row, FULL + 8 * sl); }
                    if (nst == 6) nxt = claim(&g_flags.next);
                }
#pragma unroll 1
                for (; kb < nst; kb++) {
                    take(2, bytes);
                    if (elect()) { tma3d(sm + st * SD_SL + 8192, &mp.wo, kf + kb * 32, (i & 1) * 5, FULL + 8 * st); tma2d(sm + st * SD_SL, om, kf + kb * 32, row, FULL + 8 * st); }
                    if (kb == nst - 2) nxt = claim(&g_flags.next);
                    step(2);
                }
            } else if (kind == 3) {
                take(3, 40960);
                flag_wait_warp(&g_flags.o[(2 * b + (i >> (ls + 1))) * 32], 4u << ls);
                if (elect())
                    asm volatile("cp.async.bulk.tensor.4d.shared::cluster.global.mbarrier::complete_tx::bytes.L2::cache_hint [%0], [%1, {0, 0, %3, %4}], [%2], %5;"
                        :: "r"(sm + st * SD_SL), "l"((uint64_t)&mp.ln[ls - 3]), "r"(FULL + 8 * st), "r"(i * (32 >> ls)), "r"((int)sd.slab[b]), "l"(ef) : "memory");
                step(3);
                mbar_wait(IEMPTY + 8 * (q & 3), (q >> 2) & 1);
                nxt = claim(&g_flags.next);
            } else {
                if (blockIdx.x < 96) {
                    take(3, 40960);
                    if (elect()) {
#pragma unroll 1
                        for (int c = 0; c < 5; c++) { tma2d(sm + st * SD_SL + c * 4096, &mp.wgate, blockIdx.x * 16, c * 128, FULL + 8 * st); tma2d(sm + st * SD_SL + 20480 + c * 4096, &mp.wup, blockIdx.x * 16, c * 128, FULL + 8 * st); }
                    }
                    step(3);
                }
                if (blockIdx.x < 80) {
                    take(3, 24576);
                    if (elect()) {
#pragma unroll 1
                        for (int c = 0; c < 6; c++) tma2d(sm + st * SD_SL + c * 4096, &mp.wdown, blockIdx.x * 8, c * 256, FULL + 8 * st);
                    }
                }
                if (elect()) flags_release();
                break;
            }
        }
      } else {
        const int wg = warp - 9; int ph = 0;
#pragma unroll 1
        for (int q = 0;; q++) {
            mbar_wait(IFULL + 8 * (q & 3), (q >> 2) & 1);
            const int it = __shfl_sync(0xffffffffu, lds32(IQ + 4 * (q & 3)), 0);
            if (elect()) mbar_arrive(IEMPTY + 8 * (q & 3));
            const int kind = (it >> 12) & 7, b = (it >> 8) & 15, i = it & 255;
            if (kind == 4) break;
            if (kind == 1) { if (!att) manage(); att = true; continue; }
            if ((wg == 2) != (kind == 3)) continue;
            if (kind == 3) {
                mbar_wait(LNDONE, ph); ph ^= 1;
                if (elect()) { mbar_arrive(LNFREE); flag_add(&g_flags.ln[b * 32], 32 >> sd.lsplit[b]); }
            } else {
#pragma unroll 1
                for (int rd = 0; rd < (kind == 2 ? 2 : 1); rd++) {
                    mbar_wait(EFULL + 8 * wg, ph); ph ^= 1;
                    const uint32_t src = sm + SD_EPI + wg * 24576;
                    if (elect()) {
                        const int part = kind == 2 ? rd : wg, half = kind == 2 ? wg : kind - 5;
                        if (kind) tma3d_store(part ? &mp.slab2 : &mp.slab3, (sd.slab[b] + (i >> 1)) * 128 + half * 64, (i & 1) * 5 + part * 3, src, ef, false);
                        else {
                            uint8_t* dst = g_rec + (size_t)((b * 4 + wg * 2) * NH + i) * REC;
                            bulk_s2g_ef(dst, src, 12288, ef); bulk_s2g_ef(dst + NH * REC, src + 12288, 12288, ef);
                        }
                        BULK_COMMIT();
                        BULK_WAIT_READ();
                        mbar_arrive(EEMPTY + 8 * wg);
                    }
                    __syncwarp();
                }
                if (elect()) { BULK_WAIT(); flag_add(kind == 0 ? &g_flags.v[b * 32 + i] : &g_flags.o[(2 * b + (kind == 2 ? wg : kind - 5)) * 32], kind == 2 ? 2 : 1); }
            }
            __syncwarp();
        }
      }
    } else {
        asm volatile("setmaxnreg.inc.sync.aligned.u32 200;");
        const int wg = warp >> 2, w = warp & 3;
        int st = 0, ph = 0, eph = 1, lph = 1;
        bool att = false;
        const uint32_t eb = sm + SD_EPI + wg * 24576;
        for (int q = 0;; q++) {
            mbar_wait(IFULL + 8 * (q & 3), (q >> 2) & 1);
            const int itc = __shfl_sync(0xffffffffu, lds32(IQ + 4 * (q & 3)), 0);
            if (lane == 0) mbar_arrive(IEMPTY + 8 * (q & 3));
            const int kind = (itc >> 12) & 7, b = (itc >> 8) & 15, i = itc & 255;
            const int ns = kind == 2 || kind > 4 ? 2 : 3, pad = ns == 2 ? st & 1 : (12 - st) % 3;
            if (pad) {
                mbar_wait(FULL + 8 * st, ph);
                if (lane < pad) mbar_arrive(EMPTY + 8 * (st + lane));
                st += pad; if (st == SD_NSL) { st = 0; ph ^= 1; }
            }
            const uint32_t rel = EMPTY + 8 * lane;
            if (kind == 0) {
                float acc[96];
#pragma unroll
                for (int n = 0; n < 96; n++) acc[n] = 0.f;
                int prev = -1;
                for (int kb = 0; kb < 10; kb++) {
                    FWAIT(FULL + 8 * st, ph);
                    const uint32_t base = sm + st * SD_SL;
                    WG_FENCE();
#pragma unroll
                    for (int ks = 0; ks < 4; ks++)
                        wgmma_ss_n192_tb(acc, mkdesc(base + wg * 8192 + ks * 32, 16, 1024), mkdesc(base + 16384 + ks * 2048, 8192, 1024), (kb | ks) != 0);
                    WG_COMMIT();
                    if (prev >= 0) { WG_WAIT(1); if (lane < ns) mbar_arrive(rel + 8 * prev); }
                    prev = st;
                    st += ns; if (st == SD_NSL) { st = 0; ph ^= 1; }
                }
                WG_WAIT(0);
                if (lane < ns) mbar_arrive(rel + 8 * prev);
                EPROF();
                tile_out<12, true>(acc, eb, EFULL + 8 * wg, EEMPTY + 8 * wg, eph, w, lane);
            } else if (kind == 1) {
                if (!att) {
                    bar_sync(2, 384);
                    attn_units(sm + (warp >> 1) * REC, sm + SD_EPI + (warp >> 1) * 12288 + (warp & 1) * 2048, ATT + (warp >> 1) * 64, warp & 1, lane);
                    bar_sync(2, 384);
                }
                att = true;
            } else if (kind == 2) {
                float acc[96], acc2[64];
#pragma unroll
                for (int n = 0; n < 96; n++) acc[n] = 0.f;
#pragma unroll
                for (int n = 0; n < 64; n++) acc2[n] = 0.f;
                int prev = -1;
                for (int kb = 192 >> sd.lsplit[b]; kb > 0; kb--) {
                    const uint32_t base = sm + st * SD_SL;
                    FWAIT(FULL + 8 * st, ph);
                    WG_FENCE();
#pragma unroll
                    for (int ks = 0; ks < 2; ks++) {
                        const uint64_t da = (mkdesc(base + wg * 4096 + ks * 32, 16, 512) & ~(3ull << 62)) | (2ull << 62);
                        wgmma_ss_n192_tb(acc, da, mkdesc(base + 8192 + ks * 2048, 4096, 1024), 1);
                        wgmma_ss_n128_tb(acc2, da, mkdesc(base + 8192 + 3 * 4096 + ks * 2048, 4096, 1024), 1);
                    }
                    WG_COMMIT();
                    if (prev >= 0) { WG_WAIT(1); if (lane < ns) mbar_arrive(rel + 8 * prev); }
                    prev = st;
                    st += ns; if (st == SD_NSL) { st = 0; ph ^= 1; }
                }
                WG_WAIT(0);
                if (lane < ns) mbar_arrive(rel + 8 * prev);
                EPROF();
                tile_out<12, false>(acc, eb, EFULL + 8 * wg, EEMPTY + 8 * wg, eph, w, lane);
                tile_out<8, false>(acc2, eb, EFULL + 8 * wg, EEMPTY + 8 * wg, eph, w, lane);
            } else if (kind > 4) {
                auto half = [&](auto& acc, auto mma) {
                    int prev = -1;
                    for (int kb = 192 >> sd.lsplit[b]; kb > 0; kb--) {
                        const uint32_t base = sm + st * SD_SL;
                        FWAIT(FULL + 8 * st, ph);
                        WG_FENCE();
#pragma unroll
                        for (int ks = 0; ks < 2; ks++) mma(acc, (mkdesc(base + ks * 32, 16, 512) & ~(3ull << 62)) | (2ull << 62), mkdesc(base + 8192 + wg * 12288 + ks * 2048, 4096, 1024));
                        WG_COMMIT();
                        if (prev >= 0) { WG_WAIT(1); if (lane < 2) mbar_arrive(rel + 8 * prev); }
                        prev = st;
                        st += 2; if (st == SD_NSL) { st = 0; ph ^= 1; }
                    }
                    WG_WAIT(0);
                    if (lane < 2) mbar_arrive(rel + 8 * prev);
                    EPROF();
                };
                if (wg == 0) {
                    float acc[96];
#pragma unroll
                    for (int n = 0; n < 96; n++) acc[n] = 0.f;
                    half(acc, [](float (&d)[96], uint64_t a, uint64_t bd) { wgmma_ss_n192_tb(d, a, bd, 1); });
                    tile_out<12, false>(acc, eb, EFULL, EEMPTY, eph, w, lane);
                } else {
                    float acc[64];
#pragma unroll
                    for (int n = 0; n < 64; n++) acc[n] = 0.f;
                    half(acc, [](float (&d)[64], uint64_t a, uint64_t bd) { wgmma_ss_n128_tb(d, a, bd, 1); });
                    tile_out<8, false>(acc, eb, EFULL + 8, EEMPTY + 8, eph, w, lane);
                }
            } else if (kind == 3) {
                const int ls = sd.lsplit[b], rs = 5 - ls, row = pos_row(b * 128 + (i << rs) + (warp & ((1 << rs) - 1)));
                uint2 xn[5];
#pragma unroll
                for (int q2 = 0; q2 < 5; q2++) xn[q2] = ld_ef(x + row * DM + lane * 4 + q2 * 128, ef);
                mbar_wait(VEC, 0);
                FWAIT(FULL + 8 * st, ph);
                const uint32_t base = sm + st * SD_SL;
#pragma unroll 1
                for (int c = tid; c < (320 << rs); c += 256) {
                    float a0 = 0, a1 = 0;
#pragma unroll 1
                    for (int k = 0; k < (1 << ls); k += 8) {
                        uint32_t z[8];
#pragma unroll
                        for (int u = 0; u < 8; u++) z[u] = lds32(base + c * 4 + ((k + u) * 1280 << rs));
#pragma unroll
                        for (int u = 0; u < 8; u++) { a0 += lo_f(z[u]); a1 += hi_f(z[u]); }
                    }
                    sts32(base + c * 4, pack2(a0, a1));
                }
                bar_sync(1, 256);
                uint32_t av[5][2];
#pragma unroll
                for (int q2 = 0; q2 < 5; q2++) lds64(av[q2], base + (warp & ((1 << rs) - 1)) * 1280 + lane * 8 + q2 * 256);
                PROXY_FENCE();
                __syncwarp();
                if (lane < 3) mbar_arrive(rel + 8 * st);
                st += 3; if (st == SD_NSL) { st = 0; ph ^= 1; }
                if (warp < (1 << rs)) ln2_row(av, xn, row, sm + SD_VEC + lane * 8, out, ef, lane);
                __syncwarp();
                mbar_wait(LNFREE, lph); lph ^= 1;
                if (lane == 0) mbar_arrive(LNDONE);
            } else {
                if (blockIdx.x < 96) {
                    mbar_wait(EEMPTY + 8 * wg, eph);
                    int s1 = st + 3, p1 = ph; if (s1 == SD_NSL) { s1 = 0; p1 ^= 1; }
                    side_tail(sm + st * SD_SL, FULL + 8 * st, ph, sm + s1 * SD_SL, FULL + 8 * s1, p1, sm + SD_EPI, GBAR, out, tid);
                }
                break;
            }
        }
    }
    __syncwarp();
    asm volatile("griddepcontrol.wait;" ::: "memory");
}

typedef CUresult (*EncodeFn)(CUtensorMap*, CUtensorMapDataType, cuuint32_t, void*, const cuuint64_t*, const cuuint64_t*, const cuuint32_t*, const cuuint32_t*,
                             CUtensorMapInterleave, CUtensorMapSwizzle, CUtensorMapL2promotion, CUtensorMapFloatOOBfill);
static EncodeFn s_encode = nullptr;
static void make_map(CUtensorMap* m, const void* p, int rows, int cols, int box_rows, int box_cols = 64) {
    cuuint64_t dims[2] = {(cuuint64_t)cols, (cuuint64_t)rows}, strides[1] = {(cuuint64_t)cols * 2};
    cuuint32_t box[2] = {(cuuint32_t)box_cols, (cuuint32_t)box_rows}, es[2] = {1, 1};
    s_encode(m, CU_TENSOR_MAP_DATA_TYPE_BFLOAT16, 2, (void*)p, dims, strides, box, es, CU_TENSOR_MAP_INTERLEAVE_NONE,
             box_cols == 64 ? CU_TENSOR_MAP_SWIZZLE_128B : box_cols == 32 ? CU_TENSOR_MAP_SWIZZLE_64B : CU_TENSOR_MAP_SWIZZLE_NONE, CU_TENSOR_MAP_L2_PROMOTION_L2_256B, CU_TENSOR_MAP_FLOAT_OOB_FILL_NONE);
}
static void make_map3(CUtensorMap* m, const void* p, int rows, int cols, int box_rows, int box_chunks, int cw = 64) {
    cuuint64_t dims[3] = {(cuuint64_t)cw, (cuuint64_t)rows, (cuuint64_t)cols / cw}, strides[2] = {(cuuint64_t)cols * 2, (cuuint64_t)cw * 2};
    cuuint32_t box[3] = {(cuuint32_t)cw, (cuuint32_t)box_rows, (cuuint32_t)box_chunks}, es[3] = {1, 1, 1};
    s_encode(m, CU_TENSOR_MAP_DATA_TYPE_BFLOAT16, 3, (void*)p, dims, strides, box, es, CU_TENSOR_MAP_INTERLEAVE_NONE,
             cw == 64 ? CU_TENSOR_MAP_SWIZZLE_128B : CU_TENSOR_MAP_SWIZZLE_64B, CU_TENSOR_MAP_L2_PROMOTION_L2_256B, CU_TENSOR_MAP_FLOAT_OOB_FILL_NONE);
}
template <typename T> static void* sym(T& s) { void* p = nullptr; cudaGetSymbolAddress(&p, s); return p; }

static void make_map_ln(CUtensorMap* m, const void* p, int ls) {
    cuuint64_t dims[4] = {128, 5, 128, NSLAB}, strides[3] = {256, DM * 2, 128 * DM * 2};
    cuuint32_t box[4] = {128, 5, (cuuint32_t)(32 >> ls), (cuuint32_t)(1 << ls)}, es[4] = {1, 1, 1, 1};
    s_encode(m, CU_TENSOR_MAP_DATA_TYPE_BFLOAT16, 4, (void*)p, dims, strides, box, es, CU_TENSOR_MAP_INTERLEAVE_NONE,
             CU_TENSOR_MAP_SWIZZLE_NONE, CU_TENSOR_MAP_L2_PROMOTION_L2_256B, CU_TENSOR_MAP_FLOAT_OOB_FILL_NONE);
}
static void make_sched(Sched* sd, const char* order, const char* lsplit) {
    int slab = 0, end = 0, r = 0;
    for (int b = 0; b < 16; b++) { sd->lsplit[b] = lsplit[b] - '0'; sd->slab[b] = slab; slab += 1 << sd->lsplit[b]; }
    sd->bgrows = S_TOK;
    for (; r < NRUN && order[2 * r]; r++) {
        const char k = order[2 * r], c = order[2 * r + 1]; const int b = c <= '9' ? c - '0' : c - 'a' + 10;
        sd->kind[r] = k == 'V' ? 0 : k == 'T' ? 1 : k == 'O' ? 2 : k == 'G' ? 5 : k == 'H' ? 6 : 3; sd->block[r] = b;
        end += k == 'O' || k == 'G' || k == 'H' ? 2 << sd->lsplit[b] : k == 'L' ? 4 << sd->lsplit[b] : k == 'T' ? b : 32;
        sd->end[r] = end;
        if (k == 'L') sd->bgrows -= 128;
    }
    for (; r <= NRUN; r++) { sd->end[r] = 65535; sd->kind[r] = 4; sd->block[r] = 0; }
}

extern "C" void kernel_launch(void* const* d_in, const int* in_sizes, int n_in, void* d_out, int out_size) {
    const bf16 *x = (const bf16*)d_in[0], *mem0 = (const bf16*)d_in[1], *Wq = (const bf16*)d_in[2], *Wk = (const bf16*)d_in[3],
               *Wv = (const bf16*)d_in[4], *Wo = (const bf16*)d_in[5], *wr = (const bf16*)d_in[8], *wgate = (const bf16*)d_in[9],
               *wup = (const bf16*)d_in[10], *wdown = (const bf16*)d_in[11], *c = (const bf16*)d_in[12], *wmod = (const bf16*)d_in[13];
    bf16* out = (bf16*)d_out;
    if (!s_encode) {
        cudaDriverEntryPointQueryResult qr;
        cudaGetDriverEntryPoint("cuTensorMapEncodeTiled", (void**)&s_encode, cudaEnableDefault, &qr);
        cudaFuncSetAttribute(k_side, cudaFuncAttributeMaxDynamicSharedMemorySize, SD_SMEM);
        cudaFuncSetAttribute(k_chain, cudaFuncAttributeMaxDynamicSharedMemorySize, C_SMEM);
    }
    ChainMaps cm; SideMaps sd; Sched sc;
    make_map(&sd.h, sym(g_h), S_TOK, DM, 128); make_map3(&sd.wv, Wv, DM, HD, 64, 3);
    make_map3(&sd.ost, sym(g_o), S_TOK, HD, 32, 3); make_map(&sd.o, sym(g_o), S_TOK, HD, 128, 32); make_map(&sd.o64, sym(g_o), S_TOK, HD, 64, 32); make_map3(&sd.wo, Wo, HD, DM, 32, 5);
    make_map3(&sd.slab3, sym(g_slab), NSLAB * 128, DM, 64, 3); make_map3(&sd.slab2, sym(g_slab), NSLAB * 128, DM, 64, 2);
    for (int i = 0; i < 3; i++) make_map_ln(&sd.ln[i], sym(g_slab), i + 3);
    make_map(&sd.wgate, wgate, DM, FF, 128, 16); make_map(&sd.wup, wup, DM, FF, 128, 16); make_map(&sd.wdown, wdown, FF, DM, 256, 8);
    make_map(&cm.wq, Wq, DM, HD, 128); make_map(&cm.wk, Wk, DM, HD, 128); make_map(&cm.wv, Wv, DM, HD, 128); make_map3(&cm.wo, Wo, HD, DM, 32, 7, 32);
    make_map3(&cm.h1, sym(g_h), S_TOK, DM, 32, 1); make_map3(&cm.h4, sym(g_h), S_TOK, DM, 32, 4);
    make_map(&cm.wmod, wmod, DM, 6 * DM, 160, 16);
    ChainArgs ar = {x, mem0, c, 650, 100, 0, {2, 9, 3, 0}};
    const char *order = "V0V1V2T7V3V4V5O0V6O1V7O2V8O3V9O4VaO5VbO6VcO7VdO8VeO9VfOaObOcT2OdOeGfHfLeLf",
               *lsplit = "2222222222333445";
    make_sched(&sc, order, lsplit);
    k_chain<<<96, 384, C_SMEM>>>(cm, ar);
    cudaLaunchConfig_t cfg = {};
    cfg.gridDim = dim3(N_SIDE); cfg.blockDim = dim3(512); cfg.dynamicSmemBytes = SD_SMEM; cfg.stream = cudaStreamPerThread;
    cudaLaunchAttribute at[1]; at[0].id = cudaLaunchAttributeProgrammaticStreamSerialization; at[0].val.programmaticStreamSerializationAllowed = 1;
    cfg.attrs = at; cfg.numAttrs = 1;
    cudaLaunchKernelEx(&cfg, k_side, sd, sc, x, wr, c, wmod, out);
}
```

```cpp
#include <cuda_runtime.h>
#include <cuda_bf16.h>
#include <cuda.h>
#include <stdint.h>
#include <stdio.h>
#include <string.h>
#include <stdlib.h>

typedef __nv_bfloat16 bf16;
constexpr int S_TOK = 2048, DM = 640, NH = 32, DH = 192, HD = NH * DH, NSEG = 64, SEG = 32, FF = 1536;

__device__ bf16 g_mod[6 * DM];
__device__ __align__(128) uint32_t g_modt[2 * DM];
__device__ bf16 g_h[S_TOK * DM];
constexpr int REC = 43008, R_Q = 12288, R_K = R_Q + 4096, R_KM = R_Q + 8192, R_VM = R_Q + 9216, R_J = 10240;
__device__ __align__(1024) uint8_t g_rec[(size_t)NSEG * NH * REC];
__host__ __device__ constexpr uint32_t vswz(uint32_t t) { return (t ^ (t >> 3 << 1)) & 7; }
__device__ bf16 g_o[S_TOK * HD];
__device__ bf16 g_x1[S_TOK * DM];
__device__ bf16 g_h2[S_TOK * DM];
__device__ bf16 g_r[S_TOK];
__device__ __align__(128) uint32_t g_gu[FF / 8 * 32];
__device__ __align__(1024) uint8_t g_acc[32 * 32768];
__device__ float g_slow[2 * NH * 20 * 32 * 8];
constexpr int NSLAB = 192;
__device__ bf16 g_slab[NSLAB * 128 * DM];
struct __align__(128) Flags {
    uint32_t v[16 * 32];
    uint32_t seg[64 * 32];
    uint32_t at[32 * 32];
    uint32_t o[32 * 32];
    uint32_t ln[16 * 32];
    uint32_t gu, pad1[31], slow, mod, pad3[30], anext, pad6[31], bnext, pad7[31];
    uint32_t h, pad4[31], done, pad5[31], next, pad2[31];
};
__device__ Flags g_flags;
#define LPROF(i)

__device__ __forceinline__ uint32_t smem_u32(const void* p) { return (uint32_t)__cvta_generic_to_shared(p); }
__device__ __forceinline__ uint32_t pack2(float lo, float hi) {
    uint32_t r; asm("cvt.rn.bf16x2.f32 %0, %1, %2;" : "=r"(r) : "f"(hi), "f"(lo)); return r;
}
__device__ __forceinline__ float bfr(float x) { return __uint_as_float(pack2(0.f, x)); }
__device__ __forceinline__ float inv_std(float var) {
    float s, r; asm("sqrt.approx.f32 %0, %1;" : "=f"(s) : "f"(bfr(bfr(var) + 1e-5f))); asm("rcp.approx.f32 %0, %1;" : "=f"(r) : "f"(bfr(s))); return r;
}
__device__ __forceinline__ float lo_f(uint32_t v) { return __uint_as_float(v << 16); }
__device__ __forceinline__ float hi_f(uint32_t v) { return __uint_as_float(v & 0xffff0000u); }
__device__ __forceinline__ void mbar_init(uint32_t bar, int cnt) { asm volatile("mbarrier.init.shared::cta.b64 [%0], %1;" :: "r"(bar), "r"(cnt) : "memory"); }
__device__ __forceinline__ void mbar_expect(uint32_t bar, int bytes) { asm volatile("mbarrier.arrive.expect_tx.shared::cta.b64 _, [%0], %1;" :: "r"(bar), "r"(bytes) : "memory"); }
__device__ __forceinline__ void mbar_arrive(uint32_t bar) { asm volatile("mbarrier.arrive.shared::cta.b64 _, [%0];" :: "r"(bar) : "memory"); }
constexpr int SPIN_LIMIT = 1 << 18;
__device__ __forceinline__ void mbar_wait(uint32_t bar, uint32_t par) {
    asm volatile("{ .reg .pred p, q; .reg .u32 n; mov.u32 n, 0;\n"
                 "W_%=: mbarrier.try_wait.parity.shared::cta.b64 p, [%0], %1;\n"
                 "@p bra.uni D_%=;\n"
                 "add.u32 n, n, 1; setp.lt.u32 q, n, 0x200000; @q bra.uni W_%=;\n"
                 "trap;\n"
                 "D_%=: }" :: "r"(bar), "r"(par) : "memory");
}
__device__ __forceinline__ bool mbar_test(uint32_t bar, uint32_t par) {
    uint32_t ok; asm volatile("{ .reg .pred p; mbarrier.test_wait.parity.shared::cta.b64 p, [%1], %2; selp.u32 %0, 1, 0, p; }" : "=r"(ok) : "r"(bar), "r"(par) : "memory"); return ok;
}
__device__ __forceinline__ void tma2d(uint32_t dst, const CUtensorMap* m, int c0, int c1, uint32_t bar) {
    asm volatile("cp.async.bulk.tensor.2d.shared::cluster.global.mbarrier::complete_tx::bytes [%0], [%1, {%3, %4}], [%2];"
        :: "r"(dst), "l"((uint64_t)m), "r"(bar), "r"(c0), "r"(c1) : "memory");
}
__device__ __forceinline__ uint64_t policy_stream() { uint64_t p; asm volatile("createpolicy.fractional.L2::evict_first.b64 %0, 1.0;" : "=l"(p)); return p; }
__device__ __forceinline__ void tma2d_ef(uint32_t dst, const CUtensorMap* m, int c0, int c1, uint32_t bar, uint64_t pol) {
    asm volatile("cp.async.bulk.tensor.2d.shared::cluster.global.mbarrier::complete_tx::bytes.L2::cache_hint [%0], [%1, {%3, %4}], [%2], %5;"
        :: "r"(dst), "l"((uint64_t)m), "r"(bar), "r"(c0), "r"(c1), "l"(pol) : "memory");
}
__device__ __forceinline__ void tma3d(uint32_t dst, const CUtensorMap* m, int row, int chunk, uint32_t bar) {
    asm volatile("cp.async.bulk.tensor.3d.shared::cluster.global.mbarrier::complete_tx::bytes [%0], [%1, {0, %3, %4}], [%2];"
        :: "r"(dst), "l"((uint64_t)m), "r"(bar), "r"(row), "r"(chunk) : "memory");
}
__device__ __forceinline__ void tma3d_store(const CUtensorMap* m, int row, int chunk, uint32_t src, uint64_t pol, bool hint) {
    if (hint) asm volatile("cp.async.bulk.tensor.3d.global.shared::cta.bulk_group.L2::cache_hint [%0, {0, %2, %3}], [%1], %4;"
        :: "l"((uint64_t)m), "r"(src), "r"(row), "r"(chunk), "l"(pol) : "memory");
    else asm volatile("cp.async.bulk.tensor.3d.global.shared::cta.bulk_group [%0, {0, %2, %3}], [%1];"
        :: "l"((uint64_t)m), "r"(src), "r"(row), "r"(chunk) : "memory");
}
__device__ __forceinline__ bool elect() { uint32_t p; asm volatile("{ .reg .pred e; elect.sync _|e, -1; selp.u32 %0, 1, 0, e; }" : "=r"(p)); return p; }
__device__ __forceinline__ uint2 ld_ef(const void* p, uint64_t pol) {
    uint2 v; asm volatile("ld.relaxed.gpu.global.L2::cache_hint.v2.u32 {%0,%1}, [%2], %3;" : "=r"(v.x), "=r"(v.y) : "l"(p), "l"(pol)); return v;
}
__device__ __forceinline__ void st_ef(void* p, uint2 v, uint64_t pol) {
    asm volatile("st.global.L2::cache_hint.v2.u32 [%0], {%1,%2}, %3;" :: "l"(p), "r"(v.x), "r"(v.y), "l"(pol) : "memory");
}
__device__ __forceinline__ void bulk_g2s(uint32_t dst, const void* src, int bytes, uint32_t bar) {
    asm volatile("cp.async.bulk.shared::cluster.global.mbarrier::complete_tx::bytes [%0], [%1], %2, [%3];" :: "r"(dst), "l"(src), "r"(bytes), "r"(bar) : "memory");
}
__device__ __forceinline__ void bulk_g2s_ef(uint32_t dst, const void* src, int bytes, uint32_t bar, uint64_t pol) {
    asm volatile("cp.async.bulk.shared::cluster.global.mbarrier::complete_tx::bytes.L2::cache_hint [%0], [%1], %2, [%3], %4;" :: "r"(dst), "l"(src), "r"(bytes), "r"(bar), "l"(pol) : "memory");
}
__device__ __forceinline__ void bulk_s2g(void* dst, uint32_t src, int bytes) {
    asm volatile("cp.async.bulk.global.shared::cta.bulk_group [%0], [%1], %2;" :: "l"(dst), "r"(src), "r"(bytes) : "memory");
}
__device__ __forceinline__ void bulk_s2g_ef(void* dst, uint32_t src, int bytes, uint64_t pol) {
    asm volatile("cp.async.bulk.global.shared::cta.bulk_group.L2::cache_hint [%0], [%1], %2, %3;" :: "l"(dst), "r"(src), "r"(bytes), "l"(pol) : "memory");
}
#define EF 31
#define BULK_COMMIT()    asm volatile("cp.async.bulk.commit_group;" ::: "memory")
#define BULK_WAIT_READ() asm volatile("cp.async.bulk.wait_group.read 0;" ::: "memory")
#define BULK_WAIT()      asm volatile("cp.async.bulk.wait_group 0;" ::: "memory")
#define PROXY_FENCE()    asm volatile("fence.proxy.async.shared::cta;" ::: "memory")
__device__ __forceinline__ void ldsm4(uint32_t (&r)[4], uint32_t a) {
    asm volatile("ldmatrix.sync.aligned.m8n8.x4.shared.b16 {%0,%1,%2,%3}, [%4];" : "=r"(r[0]), "=r"(r[1]), "=r"(r[2]), "=r"(r[3]) : "r"(a) : "memory");
}
__device__ __forceinline__ void ldsm4t(uint32_t (&r)[4], uint32_t a) {
    asm volatile("ldmatrix.sync.aligned.m8n8.x4.trans.shared.b16 {%0,%1,%2,%3}, [%4];" : "=r"(r[0]), "=r"(r[1]), "=r"(r[2]), "=r"(r[3]) : "r"(a) : "memory");
}
__device__ __forceinline__ void stsm4(uint32_t a, uint32_t r0, uint32_t r1, uint32_t r2, uint32_t r3) {
    asm volatile("stmatrix.sync.aligned.m8n8.x4.shared.b16 [%0], {%1,%2,%3,%4};" :: "r"(a), "r"(r0), "r"(r1), "r"(r2), "r"(r3) : "memory");
}
__device__ __forceinline__ uint32_t movm_t(uint32_t v) { uint32_t r; asm volatile("movmatrix.sync.aligned.m8n8.trans.b16 %0, %1;" : "=r"(r) : "r"(v)); return r; }
__device__ __forceinline__ void mma16(float (&d)[4], uint32_t a0, uint32_t a1, uint32_t a2, uint32_t a3, uint32_t b0, uint32_t b1) {
    asm volatile("mma.sync.aligned.m16n8k16.row.col.f32.bf16.bf16.f32 {%0,%1,%2,%3}, {%4,%5,%6,%7}, {%8,%9}, {%0,%1,%2,%3};"
        : "+f"(d[0]), "+f"(d[1]), "+f"(d[2]), "+f"(d[3]) : "r"(a0), "r"(a1), "r"(a2), "r"(a3), "r"(b0), "r"(b1));
}
__device__ __forceinline__ void mma16(float (&d)[4], const uint32_t (&a)[4], uint32_t b0, uint32_t b1) { mma16(d, a[0], a[1], a[2], a[3], b0, b1); }
__device__ __forceinline__ void mma16z(float (&d)[4], const uint32_t (&a)[4], uint32_t b0, uint32_t b1) {
    asm volatile("mma.sync.aligned.m16n8k16.row.col.f32.bf16.bf16.f32 {%0,%1,%2,%3}, {%4,%5,%6,%7}, {%8,%9}, {%10,%10,%10,%10};"
        : "=f"(d[0]), "=f"(d[1]), "=f"(d[2]), "=f"(d[3]) : "r"(a[0]), "r"(a[1]), "r"(a[2]), "r"(a[3]), "r"(b0), "r"(b1), "f"(0.f));
}
__device__ __forceinline__ void mma8z(float (&d)[4], uint32_t a0, uint32_t a1, uint32_t b0) {
    asm volatile("mma.sync.aligned.m16n8k8.row.col.f32.bf16.bf16.f32 {%0,%1,%2,%3}, {%4,%5}, {%6}, {%7,%7,%7,%7};"
        : "=f"(d[0]), "=f"(d[1]), "=f"(d[2]), "=f"(d[3]) : "r"(a0), "r"(a1), "r"(b0), "f"(0.f));
}
__device__ __forceinline__ void bar_sync(int id, int n) { asm volatile("bar.sync %0, %1;" :: "r"(id), "r"(n) : "memory"); }
__device__ __forceinline__ void bar_arrive(int id, int n) { asm volatile("bar.arrive %0, %1;" :: "r"(id), "r"(n) : "memory"); }
__device__ __forceinline__ uint64_t mkdesc(uint32_t addr, uint32_t lbo, uint32_t sbo) {
    return (uint64_t)((addr & 0x3FFFF) >> 4) | ((uint64_t)(lbo >> 4) << 16) | ((uint64_t)(sbo >> 4) << 32) | (1ull << 62);
}
#define WG_FENCE()  asm volatile("wgmma.fence.sync.aligned;" ::: "memory")
#define WG_COMMIT() asm volatile("wgmma.commit_group.sync.aligned;" ::: "memory")
#define WG_WAIT(n)  asm volatile("wgmma.wait_group.sync.aligned %0;" :: "n"(n) : "memory")

__device__ __forceinline__ void wgmma_ss_n192_tb(float (&d)[96], uint64_t a, uint64_t b, int acc) {
    asm volatile("{ .reg .pred p; setp.ne.b32 p, %98, 0;\n"
        "wgmma.mma_async.sync.aligned.m64n192k16.f32.bf16.bf16 {%0,%1,%2,%3,%4,%5,%6,%7,%8,%9,%10,%11,%12,%13,%14,%15,%16,%17,%18,%19,%20,%21,%22,%23,%24,%25,%26,%27,%28,%29,%30,%31,%32,%33,%34,%35,%36,%37,%38,%39,%40,%41,%42,%43,%44,%45,%46,%47,%48,%49,%50,%51,%52,%53,%54,%55,%56,%57,%58,%59,%60,%61,%62,%63,%64,%65,%66,%67,%68,%69,%70,%71,%72,%73,%74,%75,%76,%77,%78,%79,%80,%81,%82,%83,%84,%85,%86,%87,%88,%89,%90,%91,%92,%93,%94,%95}, %96, %97, p, 1, 1, 0, 1; }"
        : "+f"(d[0]), "+f"(d[1]), "+f"(d[2]), "+f"(d[3]), "+f"(d[4]), "+f"(d[5]), "+f"(d[6]), "+f"(d[7]), "+f"(d[8]), "+f"(d[9]), "+f"(d[10]), "+f"(d[11]), "+f"(d[12]), "+f"(d[13]), "+f"(d[14]), "+f"(d[15]), "+f"(d[16]), "+f"(d[17]), "+f"(d[18]), "+f"(d[19]), "+f"(d[20]), "+f"(d[21]), "+f"(d[22]), "+f"(d[23]), "+f"(d[24]), "+f"(d[25]), "+f"(d[26]), "+f"(d[27]), "+f"(d[28]), "+f"(d[29]), "+f"(d[30]), "+f"(d[31]), "+f"(d[32]), "+f"(d[33]), "+f"(d[34]), "+f"(d[35]), "+f"(d[36]), "+f"(d[37]), "+f"(d[38]), "+f"(d[39]), "+f"(d[40]), "+f"(d[41]), "+f"(d[42]), "+f"(d[43]), "+f"(d[44]), "+f"(d[45]), "+f"(d[46]), "+f"(d[47]), "+f"(d[48]), "+f"(d[49]), "+f"(d[50]), "+f"(d[51]), "+f"(d[52]), "+f"(d[53]), "+f"(d[54]), "+f"(d[55]), "+f"(d[56]), "+f"(d[57]), "+f"(d[58]), "+f"(d[59]), "+f"(d[60]), "+f"(d[61]), "+f"(d[62]), "+f"(d[63]), "+f"(d[64]), "+f"(d[65]), "+f"(d[66]), "+f"(d[67]), "+f"(d[68]), "+f"(d[69]), "+f"(d[70]), "+f"(d[71]), "+f"(d[72]), "+f"(d[73]), "+f"(d[74]), "+f"(d[75]), "+f"(d[76]), "+f"(d[77]), "+f"(d[78]), "+f"(d[79]), "+f"(d[80]), "+f"(d[81]), "+f"(d[82]), "+f"(d[83]), "+f"(d[84]), "+f"(d[85]), "+f"(d[86]), "+f"(d[87]), "+f"(d[88]), "+f"(d[89]), "+f"(d[90]), "+f"(d[91]), "+f"(d[92]), "+f"(d[93]), "+f"(d[94]), "+f"(d[95])
        : "l"(a), "l"(b), "r"(acc));
}

__device__ __forceinline__ void wgmma_ss_n128_tb(float (&d)[64], uint64_t a, uint64_t b, int acc) {
    asm volatile("{ .reg .pred p; setp.ne.b32 p, %66, 0;\n"
        "wgmma.mma_async.sync.aligned.m64n128k16.f32.bf16.bf16 {%0,%1,%2,%3,%4,%5,%6,%7,%8,%9,%10,%11,%12,%13,%14,%15,%16,%17,%18,%19,%20,%21,%22,%23,%24,%25,%26,%27,%28,%29,%30,%31,%32,%33,%34,%35,%36,%37,%38,%39,%40,%41,%42,%43,%44,%45,%46,%47,%48,%49,%50,%51,%52,%53,%54,%55,%56,%57,%58,%59,%60,%61,%62,%63}, %64, %65, p, 1, 1, 0, 1; }"
        : "+f"(d[0]), "+f"(d[1]), "+f"(d[2]), "+f"(d[3]), "+f"(d[4]), "+f"(d[5]), "+f"(d[6]), "+f"(d[7]), "+f"(d[8]), "+f"(d[9]), "+f"(d[10]), "+f"(d[11]), "+f"(d[12]), "+f"(d[13]), "+f"(d[14]), "+f"(d[15]), "+f"(d[16]), "+f"(d[17]), "+f"(d[18]), "+f"(d[19]), "+f"(d[20]), "+f"(d[21]), "+f"(d[22]), "+f"(d[23]), "+f"(d[24]), "+f"(d[25]), "+f"(d[26]), "+f"(d[27]), "+f"(d[28]), "+f"(d[29]), "+f"(d[30]), "+f"(d[31]), "+f"(d[32]), "+f"(d[33]), "+f"(d[34]), "+f"(d[35]), "+f"(d[36]), "+f"(d[37]), "+f"(d[38]), "+f"(d[39]), "+f"(d[40]), "+f"(d[41]), "+f"(d[42]), "+f"(d[43]), "+f"(d[44]), "+f"(d[45]), "+f"(d[46]), "+f"(d[47]), "+f"(d[48]), "+f"(d[49]), "+f"(d[50]), "+f"(d[51]), "+f"(d[52]), "+f"(d[53]), "+f"(d[54]), "+f"(d[55]), "+f"(d[56]), "+f"(d[57]), "+f"(d[58]), "+f"(d[59]), "+f"(d[60]), "+f"(d[61]), "+f"(d[62]), "+f"(d[63])
        : "l"(a), "l"(b), "r"(acc));
}

__device__ __forceinline__ void wgmma_rs_n32(float (&d)[16], const uint32_t (&a)[4], uint64_t b) {
    asm volatile("wgmma.mma_async.sync.aligned.m64n32k16.f32.bf16.bf16 {%0,%1,%2,%3,%4,%5,%6,%7,%8,%9,%10,%11,%12,%13,%14,%15}, {%16,%17,%18,%19}, %20, 1, 1, 1, 0;"
        : "+f"(d[0]), "+f"(d[1]), "+f"(d[2]), "+f"(d[3]), "+f"(d[4]), "+f"(d[5]), "+f"(d[6]), "+f"(d[7]), "+f"(d[8]), "+f"(d[9]), "+f"(d[10]), "+f"(d[11]), "+f"(d[12]), "+f"(d[13]), "+f"(d[14]), "+f"(d[15])
        : "r"(a[0]), "r"(a[1]), "r"(a[2]), "r"(a[3]), "l"(b));
}
__device__ __forceinline__ uint32_t umax3(uint32_t a, uint32_t b, uint32_t c) { return max(max(a, b), c); }
__device__ __forceinline__ void wait_until(uint32_t t) { while ((int32_t)((uint32_t)clock() - t) < 0) {} }
__device__ __forceinline__ uint32_t gtime() { uint32_t c; asm volatile("mov.u32 %0, %%globaltimer_lo;" : "=r"(c)); return c; }
__device__ __forceinline__ uint32_t opaque(uint32_t v) { uint32_t r; asm volatile("shfl.sync.bfly.b32 %0, %1, 0, 31, -1;" : "=r"(r) : "r"(v)); return r; }
__device__ __forceinline__ uint32_t lds32(uint32_t a) { uint32_t v; asm volatile("ld.shared.u32 %0, [%1];" : "=r"(v) : "r"(a) : "memory"); return v; }
__device__ __forceinline__ void sts32(uint32_t a, uint32_t v) { asm volatile("st.shared.u32 [%0], %1;" :: "r"(a), "r"(v) : "memory"); }
__device__ __forceinline__ void lds64(uint32_t (&v)[2], uint32_t a) { asm volatile("ld.shared.v2.u32 {%0,%1}, [%2];" : "=r"(v[0]), "=r"(v[1]) : "r"(a) : "memory"); }
__device__ __forceinline__ void lds128(uint32_t (&v)[4], uint32_t a) { asm volatile("ld.shared.v4.u32 {%0,%1,%2,%3}, [%4];" : "=r"(v[0]), "=r"(v[1]), "=r"(v[2]), "=r"(v[3]) : "r"(a) : "memory"); }
__device__ __forceinline__ void sts128(uint32_t a, uint32_t x, uint32_t y, uint32_t z, uint32_t w) { asm volatile("st.shared.v4.u32 [%0], {%1,%2,%3,%4};" :: "r"(a), "r"(x), "r"(y), "r"(z), "r"(w) : "memory"); }
__device__ __forceinline__ float2 lds64f(uint32_t a) { float2 v; asm volatile("ld.shared.v2.f32 {%0,%1}, [%2];" : "=f"(v.x), "=f"(v.y) : "r"(a) : "memory"); return v; }
__device__ __forceinline__ float4 lds128f(uint32_t a) { float4 v; asm volatile("ld.shared.v4.f32 {%0,%1,%2,%3}, [%4];" : "=f"(v.x), "=f"(v.y), "=f"(v.z), "=f"(v.w) : "r"(a) : "memory"); return v; }
__device__ __forceinline__ void sts128f(uint32_t a, float x, float y, float z, float w) { asm volatile("st.shared.v4.f32 [%0], {%1,%2,%3,%4};" :: "r"(a), "f"(x), "f"(y), "f"(z), "f"(w) : "memory"); }

__device__ __forceinline__ float warp_sum(float v) {
#pragma unroll
    for (int o = 16; o; o >>= 1) v += __shfl_xor_sync(0xffffffffu, v, o);
    return v;
}
__device__ __forceinline__ uint32_t badd(uint32_t a, uint32_t b) { uint32_t r; asm("add.rn.bf16x2 %0, %1, %2;" : "=r"(r) : "r"(a), "r"(b)); return r; }
__device__ __forceinline__ uint32_t bsub(uint32_t a, uint32_t b) { uint32_t r; asm("sub.rn.bf16x2 %0, %1, %2;" : "=r"(r) : "r"(a), "r"(b)); return r; }
__device__ __forceinline__ uint32_t bmul(uint32_t a, uint32_t b) { uint32_t r; asm("mul.rn.bf16x2 %0, %1, %2;" : "=r"(r) : "r"(a), "r"(b)); return r; }
__device__ __forceinline__ uint32_t silu2(uint32_t v) { return pack2(__fdividef(lo_f(v), 1.f + __expf(-lo_f(v))), __fdividef(hi_f(v), 1.f + __expf(-hi_f(v)))); }
__device__ __forceinline__ void ln_row(const uint32_t (&x)[10], uint32_t (&n)[10]) {
    float s0 = 0, s1 = 0;
#pragma unroll
    for (int i = 0; i < 10; i++) { s0 += lo_f(x[i]); s1 += hi_f(x[i]); }
    const float mean = warp_sum(s0 + s1) * (1.f / DM);
    float q0 = 0, q1 = 0;
#pragma unroll
    for (int i = 0; i < 10; i++) { const float d0 = lo_f(x[i]) - mean, d1 = hi_f(x[i]) - mean; q0 += d0 * d0; q1 += d1 * d1; }
    const uint32_t mb = pack2(mean, mean);
    const float inv = inv_std(warp_sum(q0 + q1) * (1.f / DM));
#pragma unroll
    for (int i = 0; i < 10; i++) { const uint32_t d = bsub(x[i], mb); n[i] = pack2(lo_f(d) * inv, hi_f(d) * inv); }
}
__device__ __forceinline__ uint32_t ld_rlx(const uint32_t* f) { uint32_t v; asm volatile("ld.relaxed.gpu.global.u32 %0, [%1];" : "=r"(v) : "l"(f) : "memory"); return v; }
__device__ __forceinline__ void flag_wait(const uint32_t* f, uint32_t target) {
    for (int n = 0;; n++) {
        uint32_t v; asm volatile("ld.relaxed.gpu.global.u32 %0, [%1];" : "=r"(v) : "l"(f) : "memory");
        if (v >= target) break;
        if (n > (1 << 23)) __trap();
    }
}
#define NAP 100
__device__ __forceinline__ void flag_wait_warp(const uint32_t* f, uint32_t target) {
    for (int n = 0; !__all_sync(0xffffffffu, ld_rlx(f) >= target); n++) { if (NAP) __nanosleep(NAP); if (n > (1 << 23)) __trap(); }
}
__device__ __forceinline__ void flag_add(uint32_t* f, uint32_t v = 1) { asm volatile("red.release.gpu.global.add.u32 [%0], %1;" :: "l"(f), "r"(v) : "memory"); }
constexpr int N_SIDE = 132;
__device__ __forceinline__ void flags_release() {
    uint32_t old; asm volatile("atom.acq_rel.gpu.global.add.u32 %0, [%1], 1;" : "=r"(old) : "l"(&g_flags.done) : "memory");
    if (old == 96 + N_SIDE - 1) { g_flags.h = 0; g_flags.next = 0; g_flags.done = 0; }
}

struct ChainMaps { CUtensorMap wq, wk, wv, wo, h1, h4, wmod; };
struct ChainArgs { const bf16 *x, *mem0, *c; int D, D2, force, P[4]; };
constexpr uint32_t SM_BASE = 1024;
constexpr int C_WV = 0, C_WO = 81920, C_XR = 167936, C_QX = C_XR + 4 * 4096, C_KX = C_XR + 9 * 4096, C_VX = C_XR + 40960, C_MEM = C_VX + 4096, C_VP = C_MEM,
              C_QM = C_MEM + 10240, C_KM = C_QM + 1024, C_VM = C_KM + 1024, C_OX = C_VM + 1024, C_SC = C_OX + 3072, C_BAR = C_SC + 1920, C_SMEM = C_BAR + 256;
constexpr int CB_W = C_BAR, CB_W2 = C_BAR + 8, CB_SC = C_BAR + 16, CB_OX = C_BAR + 24, CB_VX = C_BAR + 32, CB_XF = C_BAR + 40, CB_XG = C_BAR + 48, CB_PRE = C_BAR + 56, CB_WK = C_BAR + 64, CB_PC = C_BAR + 96,
              C_MAX = C_BAR + 128, C_SCL = C_BAR + 144, C_BAD = C_BAR + 148, C_TW = C_BAR + 152;
static_assert(C_SMEM <= 232448, "chain shared memory");
enum { B_MEM = 1, B_QK, B_VP, B_OWN, B_RED, B_X, B_AUX, B_VM, B_X2, B_T };
constexpr int NP = 8;
constexpr int NW = 8;
#define VD 2
#define S_NOW 58
#define WLATE 1
#define VPB 0
#define VPRE 1
#define BX 3
constexpr int OD = 4;
#define TRACE0 ((uint32_t*)nullptr)
#define PROF(i)
#define PROFG(i)
#define PROFV(i, v)
#define SFENCE() asm volatile("griddepcontrol.launch_dependents;" ::: "memory")
#define PIN(x) asm volatile("" : "+r"(x))
#define PINL(x) asm volatile("" : "+l"(x))
__host__ __device__ constexpr bool pair_v(int i) { return i == 0 || (i % 3 == 2 && i < 9); }
__host__ __device__ constexpr bool pair_own(int i) { return pair_v(i) || i >= 14; }
__host__ __device__ constexpr int pair_idx(int i) { return pair_v(i) ? (i + 1) / 3 : i < 14 ? i - (i < 9 ? i / 3 + 1 : 4) : i - 10; }
__host__ __device__ constexpr int pair_ld(int i) { return i + 2 + (i / 3 < BX ? i / 3 : BX) < 20 ? i + 2 + (i / 3 < BX ? i / 3 : BX) : 20; }

__device__ __forceinline__ uint32_t packh(float lo, float hi) { uint32_t r; asm("cvt.rn.f16x2.f32 %0, %1, %2;" : "=r"(r) : "f"(hi), "f"(lo)); return r; }
__device__ __forceinline__ uint32_t h2b(uint32_t v) {
    uint32_t r; asm("{ .reg .f16 a, b; .reg .f32 x, y; mov.b32 {a, b}, %1; cvt.f32.f16 x, a; cvt.f32.f16 y, b; cvt.rn.bf16x2.f32 %0, y, x; }" : "=r"(r) : "r"(v)); return r;
}
__device__ __forceinline__ uint32_t h2b_lo(uint32_t u, uint32_t v) {
    uint32_t r; asm("{ .reg .f16 a, b, c, d; .reg .f32 x, y; mov.b32 {a, b}, %1; mov.b32 {c, d}, %2; cvt.f32.f16 x, a; cvt.f32.f16 y, c; cvt.rn.bf16x2.f32 %0, y, x; }" : "=r"(r) : "r"(u), "r"(v)); return r;
}
constexpr float SCL2E = 0.07216878364870322f * 1.4426950408889634f;
__device__ __forceinline__ uint32_t score_tile(const uint32_t (&qa)[2][4], const uint32_t (&kb)[2][4]) {
    float u[4], v[4], x[4], y[4];
    mma16z(u, qa[0], kb[0][0], kb[0][1]); mma16z(v, qa[0], kb[0][2], kb[0][3]);
    mma16z(x, qa[1], kb[1][0], kb[1][1]); mma16z(y, qa[1], kb[1][2], kb[1][3]);
    return pack2(((u[0] + v[2]) + (x[0] + y[2])) * SCL2E, ((u[1] + v[3]) + (x[1] + y[3])) * SCL2E);
}
__device__ __forceinline__ void score_tiles(const uint32_t (&qa)[2][4], const uint32_t (&kb)[2][4], const uint32_t (&km)[2][4], uint32_t& a, uint32_t& b) {
    float u[4], v[4], x[4], y[4];
    mma16z(u, qa[0], kb[0][0], kb[0][1]); mma16z(v, qa[0], kb[0][2], kb[0][3]); mma16z(x, qa[0], km[0][0], km[0][1]); mma16z(y, qa[0], km[0][2], km[0][3]);
    mma16(u, qa[1], kb[1][0], kb[1][1]); mma16(v, qa[1], kb[1][2], kb[1][3]); mma16(x, qa[1], km[1][0], km[1][1]); mma16(y, qa[1], km[1][2], km[1][3]);
    a = pack2((u[0] + v[2]) * SCL2E, (u[1] + v[3]) * SCL2E); b = pack2((x[0] + y[2]) * SCL2E, (x[1] + y[3]) * SCL2E);
}
__device__ __forceinline__ void stas1(uint32_t dst, uint32_t x, uint32_t bar) {
    asm volatile("st.async.shared::cluster.mbarrier::complete_tx::bytes.b32 [%0], %1, [%2];" :: "r"(dst), "r"(x), "r"(bar) : "memory");
}
__device__ __forceinline__ void stas2(uint32_t dst, uint32_t x, uint32_t y, uint32_t bar) {
    asm volatile("st.async.shared::cluster.mbarrier::complete_tx::bytes.v2.b32 [%0], {%1,%2}, [%3];" :: "r"(dst), "r"(x), "r"(y), "r"(bar) : "memory");
}
__device__ __forceinline__ float ex2(float x) { float r; asm volatile("ex2.approx.ftz.f32 %0, %1;" : "=f"(r) : "f"(x)); return r; }
__device__ __forceinline__ void h_fetch_a(const ChainMaps& mp, uint32_t sm, int n) {
    mbar_expect(sm + CB_XF, 32768);
    tma3d(sm + C_XR, &mp.h4, n * SEG, 0, sm + CB_XF); tma3d(sm + C_XR + 20480, &mp.h4, n * SEG, 5, sm + CB_XF);
}
__device__ __forceinline__ void h_fetch_b(const ChainMaps& mp, uint32_t sm, int n) {
    mbar_expect(sm + CB_XG, 8192);
    tma3d(sm + C_QX, &mp.h1, n * SEG, 4, sm + CB_XG); tma3d(sm + C_KX, &mp.h1, n * SEG, 9, sm + CB_XG);
}
__device__ __forceinline__ uint32_t absmax2(uint32_t a, uint32_t b) {
    uint32_t r; asm("max.u16x2 %0, %1, %2;" : "=r"(r) : "r"(a), "r"(b & 0x7fff7fffu)); return r;
}

__global__ void __cluster_dims__(3, 1, 1) __launch_bounds__(384, 1) k_chain(const __grid_constant__ ChainMaps mp, const __grid_constant__ ChainArgs ar) {
    extern __shared__ __align__(1024) uint8_t smraw[];
    const uint32_t sm = SM_BASE + ((blockIdx.x % 3) << 24);
    if (smem_u32(smraw) != sm) __trap();
    uint32_t tid; asm volatile("mov.u32 %0, %%tid.x;" : "=r"(tid));
    const int warp = __shfl_sync(0xffffffffu, tid >> 5, 0), lane = tid & 31, wg = warp >> 2, w = warp & 3;
    const int blk = blockIdx.x, head = blk / 3, j = blk % 3;
    const int col0 = head * DH + j * 64, u0 = 7 * j, nu = j == 2 ? 6 : 7;
    asm volatile("griddepcontrol.launch_dependents;");
#define PPROF(i)
#define PPROF2(i)
    PPROF(0);
    const int r = lane & 7, mi = lane >> 3;
    {
        if (warp == 11) {
            if (lane < 16) mbar_init(sm + C_BAR + 8 * lane, lane == 2 ? 5 : 1);
            asm volatile("fence.mbarrier_init.release.cluster;" ::: "memory");
            __syncwarp();
            if (elect()) {
                mbar_expect(sm + CB_PRE, (blk < 80 ? 20480 : 0) + 10240);
                if (blk < 80) {
#pragma unroll 1
                    for (int c = 0; c < 4; c++) tma2d(sm + C_XR + c * 5120, &mp.wmod, blk * 16, c * 160, sm + CB_PRE);
                }
                bulk_g2s(sm + C_XR + 20480, ar.mem0, 10240, sm + CB_PRE);
                mbar_expect(sm + CB_SC, 1280); mbar_expect(sm + CB_OX, 2048);
            }
            __syncwarp();
            asm volatile("barrier.cluster.arrive.relaxed.aligned; barrier.cluster.wait.aligned;" ::: "memory");
        } else {
        const int row0 = blk * 11 + warp; const bool two = row0 < S_TOK - 1056;
        uint32_t xv[2][10], cv[8];
#pragma unroll
        for (int i = 0; i < 8; i++) cv[i] = __ldg((const uint32_t*)ar.c + (warp < 10 ? warp : 0) * 32 + i * 4 + (lane & 3));
#pragma unroll
        for (int i = 0; i < 10; i++) {
            const uint2 v = __ldg((const uint2*)(ar.x + (row0 + (i >= 5 && two ? 1056 : 0)) * DM) + lane + i % 5 * 32);
            xv[i / 5][2 * (i % 5)] = v.x; xv[i / 5][2 * (i % 5) + 1] = v.y;
        }
        asm volatile("barrier.cluster.arrive.relaxed.aligned;" ::: "memory");
#pragma unroll 1
        for (int i = blk * 352 + tid; i < 32 * 1600; i += 96 * 352) ((uint4*)g_acc)[i / 1600 * 2048 + i % 1600] = make_uint4(0, 0, 0, 0);
        if (tid < 16 && blk * 16 + tid < (int)(offsetof(Flags, h) / 16)) ((uint4*)&g_flags)[blk * 16 + tid] = make_uint4(0, 0, 0, 0);
        static_assert(offsetof(Flags, h) <= 96 * 16 * 16, "flags");
        PPROF(8);
        asm volatile("barrier.cluster.wait.aligned;" ::: "memory");
        PPROF(9);
#pragma unroll
        for (int i = 0; i < 8; i++) cv[i] = silu2(cv[i]);
        mbar_wait(sm + CB_PRE, 0);
        PPROF(10);
        if (warp < 10) {
            float d[4] = {0, 0, 0, 0};
#pragma unroll
            for (int k = 0; k < 4; k++) { uint32_t a[4]; ldsm4t(a, sm + C_XR + ((warp * 4 + k) * 16 + (mi >> 1) * 8 + r) * 32 + (mi & 1) * 16); mma16(d, a, cv[2 * k], cv[2 * k + 1]); }
            if ((lane & 3) == 0) { sts32(sm + C_QM + warp * 64 + lane, __float_as_uint(d[0])); sts32(sm + C_QM + warp * 64 + 32 + lane, __float_as_uint(d[2])); }
        }
        bar_sync(B_MEM, 352);
        PPROF(11);
        if (tid < 16 && blk < 80) {
            float a = 0;
#pragma unroll
            for (int i = 0; i < 10; i++) a += __uint_as_float(lds32(sm + C_QM + i * 64 + tid * 4));
            asm volatile("st.relaxed.gpu.global.u32 [%0], %1;" :: "l"(g_modt + blk * 16 + tid), "r"(pack2(0.f, a) | 1u) : "memory");
        }
        PPROF(1);
#pragma unroll 1
        for (int q = 0; q < 2; q++) {
            uint32_t n[10]; ln_row(xv[0], n);
#pragma unroll
            for (int i = 0; i < 10; i++) { xv[0][i] = xv[1][i]; xv[1][i] = n[i]; }
        }
        if (tid < 320) {
            uint32_t v[4];
            for (int n = 0;; n++) {
                asm volatile("ld.relaxed.gpu.global.v4.u32 {%0,%1,%2,%3}, [%4];" : "=r"(v[0]), "=r"(v[1]), "=r"(v[2]), "=r"(v[3]) : "l"(g_modt + tid * 4) : "memory");
                if (__all_sync(0xffffffffu, v[0] & v[1] & v[2] & v[3] & 1)) break;
                if (n > (1 << 22)) __trap();
            }
            asm volatile("st.shared.v2.u32 [%0], {%1,%2};" :: "r"(sm + C_VX + tid * 8), "r"(__byte_perm(v[0], v[1], 0x7632)), "r"(__byte_perm(v[2], v[3], 0x7632)) : "memory");
        }
        bar_sync(B_MEM, 352);
        PPROF(2);
#pragma unroll
        for (int i = 0; i < 5; i++) {
            uint32_t sh[2], sc[2]; lds64(sh, sm + C_VX + lane * 8 + i * 256); lds64(sc, sm + C_VX + 1280 + lane * 8 + i * 256);
            sc[0] = badd(sc[0], 0x3f803f80u); sc[1] = badd(sc[1], 0x3f803f80u);
#pragma unroll
            for (int q = 0; q < 2; q++)
                if (q == 0 || two) ((uint2*)(g_h + (row0 + q * 1056) * DM))[lane + i * 32] = make_uint2(badd(bmul(xv[q][2 * i], sc[0]), sh[0]), badd(bmul(xv[q][2 * i + 1], sc[1]), sh[1]));
        }
        if (warp < 10) {
#pragma unroll
            for (int i = 0; i < 2; i++) {
                uint32_t v[4]; ldsm4t(v, sm + C_XR + 20480 + r * 1280 + ((warp * 2 + i) * 4 + mi) * 16);
                stsm4(sm + C_MEM + (warp * 2 + i) * 512 + lane * 16, v[0], v[1], v[2], v[3]);
            }
        }
        bar_sync(B_MEM, 352);
        PPROF(3);
        }
    }
    uint8_t* const rec0 = g_rec + (size_t)head * REC;
    if (wg < 2) {
        asm volatile("setmaxnreg.inc.sync.aligned.u32 224;");
        const uint32_t l16 = opaque(sm + lane * 16);
        uint32_t wa[40][4], pl[NP][4];
        const uint32_t wfrag = ((mi >> 1) * 8 + r) * 128 + (((2 * w + (mi & 1)) ^ r) << 4);
        mbar_wait(sm + (wg ? CB_WK : CB_W), 0);
#pragma unroll
        for (int i = 0; i < 40; i++)
            ldsm4t(wa[i], sm + (wg == 0 ? C_WV : C_WO) + wfrag + ((pair_own(i >> 1) ? wg : 1 - wg) * 20 + pair_idx(i >> 1) * 2 + (i & 1)) * 2048);
        PPROF(5);
        PROXY_FENCE();
        if (wg) bar_arrive(B_VM, 160); else bar_arrive(B_OWN, 160);
        const uint32_t wvrd = opaque(sm + C_WV + wfrag + wg * 40960);
        const uint32_t word = opaque(sm + C_WO + warp * 2048 + ((mi >> 1) * 8 + r) * 64 + (((mi & 1) ^ (r >> 1)) << 4));
        const uint32_t own = wg * 5120, oth = 5120 - own;
        const uint32_t mo = l16 + C_MEM + own, mt = l16 + C_MEM + oth;
        uint32_t b0[2][4];
        auto start = [&]() { bar_sync(B_MEM, 384); ldsm4t(b0[0], mo); ldsm4t(b0[1], mt); };
        auto x_part = [&](int n_, uint64_t xo, uint64_t xt, bool pool, uint32_t* trace) {
            float acc[16];
#pragma unroll
            for (int i = 0; i < 16; i++) acc[i] = 0.f;
            if (warp == 1) PROF(12);
            WG_FENCE();
#pragma unroll
            for (int n = 0; n < 40; n++) {
                const int i = n < 24 ? n : n < 32 ? n + 4 : n < 36 ? n - 8 : n, ks = pair_idx(i >> 1) * 2 + (i & 1);
                if (n == 32) mbar_wait(sm + CB_XG, n_ & 1);
                wgmma_rs_n32(acc, wa[i], (pair_own(i >> 1) ? xo : xt) + (((ks >> 2) * 4096 + (ks & 3) * 32) >> 4));
                if (pool && n % 4 == 2 && n / 4 < NP) { SFENCE(); ldsm4t(pl[n / 4], wvrd + n / 4 * 2048); }
                if (n == 35) WG_COMMIT();
            }
            WG_COMMIT();
            uint32_t dst = l16; PIN(dst); dst = (dst ^ (dst >> 3 & 48)) + wg * 20480 + w * 1024; PIN(dst);
            WG_WAIT(1);
            if (wg) bar_arrive(B_X, 256); else bar_arrive(B_X2, 256);
            WG_WAIT(0);
            if (warp == 1) PROF(13);
            if (wg) bar_sync(B_X2, 256); else bar_sync(B_X, 256);
            sts128(dst + C_QX, pack2(acc[0], acc[1]), pack2(acc[4], acc[5]), pack2(acc[8], acc[9]), pack2(acc[12], acc[13]));
            sts128(dst + C_QX + 512, pack2(acc[2], acc[3]), pack2(acc[6], acc[7]), pack2(acc[10], acc[11]), pack2(acc[14], acc[15]));
            if (warp == 1) PROF(14);
        };
        mbar_wait(sm + CB_XF, 0);
        x_part(0, mkdesc(SM_BASE + C_XR + wg * 20480, 16, 1024), mkdesc(SM_BASE + C_XR + 20480 - wg * 20480, 16, 1024), false, TRACE0);
        PPROF(6);
        mbar_wait(sm + CB_W2, 0);
        PPROF(7);
#pragma unroll
        for (int i = 0; i < NP; i++) ldsm4t(pl[i], wvrd + i * 2048);
        start();
#pragma unroll 1
        for (int s = 0;;) {
            uint32_t* trace = TRACE0 + s * 32;
            uint64_t xo = mkdesc(SM_BASE + C_XR + wg * 20480, 16, 1024), xt = mkdesc(SM_BASE + C_XR + 20480 - wg * 20480, 16, 1024);
            {
                float dv[2][4], d[4][4], u[4], isc;
                uint32_t b[20][4], av[20][4], l4;
#pragma unroll
                for (int i = 0; i < 8; i++) b[i >> 2][i & 3] = b0[i >> 2][i & 3];
                if (warp == 0) { PROF(0); PROFG(24); }
#pragma unroll
                for (int i = 0; i < 20; i++) {
                    const int c = i < 3 ? 0 : (i & 1) * 2, p = 2 * pair_idx(i);
                    if (i) SFENCE();
#pragma unroll
                    for (int e = 0; e < 2; e++) { const int n = (i ? pair_ld(i - 1) : 2) + e; if (n < pair_ld(i)) ldsm4t(b[n], (pair_own(n) ? mo : mt) + pair_idx(n) * 512); }
                    if (i >= 18 - VPRE && i < 18) ldsm4t(av[NP + i - (18 - VPRE)], wvrd + (NP + i - (18 - VPRE)) * 2048);
                    if (i > 0 && pair_v(i)) { mma16(dv[0], pl[p % NP], b[i][0], b[i][1]); mma16(dv[1], pl[(p + 1) % NP], b[i][2], b[i][3]); }
                    if (i == 0 || i == 3) { mma16z(d[c], wa[2 * i], b[i][0], b[i][1]); mma16z(d[c + 1], wa[2 * i + 1], b[i][2], b[i][3]); }
                    else { mma16(d[c], wa[2 * i], b[i][0], b[i][1]); mma16(d[c + 1], wa[2 * i + 1], b[i][2], b[i][3]); }
                    if (i == 0) { mma16z(dv[0], pl[0], b[i][0], b[i][1]); mma16z(dv[1], pl[1], b[i][2], b[i][3]); }
                    if (i == 12) isc = __uint_as_float(lds32(sm + C_SCL));
                    if (i == 17) { l4 = l16; PIN(l4); l4 = (l4 >> 2) & 127; PIN(l4); }
                }
                SFENCE();
#pragma unroll
                for (int i = 0; i < 4; i++) u[i] = fmaf(d[2][i] + d[3][i], isc, (d[0][i] + d[1][i]) * isc);
                const uint32_t qs = sm + C_QM + warp * 256 + l4;
                sts32(qs, pack2(u[0], u[1])); sts32(qs + 128, pack2(u[2], u[3]));
                if (warp == 2) PROF(1);
                bar_sync(B_QK, 384);
                const uint32_t bad = lds32(sm + C_BAD);
                PROXY_FENCE();
                if (bad) {
                    if (warp < nu) {
                        float e[2][4] = {{0, 0, 0, 0}, {0, 0, 0, 0}};
#pragma unroll 1
                        for (int k = 0; k < 12; k++) {
                            uint32_t ob[2]; lds64(ob, sm + C_OX + k * 256 + l4 * 2);
                            ldsm4t(pl[0], word + (k >> 1) * 14336 + (k & 1) * 1024); ldsm4t(pl[1], (word ^ 32) + (k >> 1) * 14336 + (k & 1) * 1024);
                            mma16(e[0], pl[0], ob[0], ob[1]); mma16(e[1], pl[1], ob[0], ob[1]);
                        }
                        float4* dst = (float4*)(g_slow + (((s & 1) * NH + head) * 20 + u0 + warp) * 256 + l4 * 2);
                        dst[0] = make_float4(e[0][0] * isc, e[0][1] * isc, e[0][2] * isc, e[0][3] * isc); dst[1] = make_float4(e[1][0] * isc, e[1][1] * isc, e[1][2] * isc, e[1][3] * isc);
                        __threadfence();
                    }
                    bar_arrive(B_RED, 384);
#pragma unroll
                    for (int i = 0; i < NP; i++) ldsm4t(pl[i], wvrd + i * 2048);
                    start();
                    continue;
                }
                {
#pragma unroll
                    for (int f = NP + VPRE; f < NP + VPRE + VD; f++) ldsm4t(av[f], wvrd + f * 2048);
#pragma unroll
                    for (int f = NP; f < 20; f++) {
                        if (f >= NP + VPRE) SFENCE();
                        if (f >= NP + VPRE && f + VD < 20) ldsm4t(av[f + VD], wvrd + (f + VD) * 2048);
                        mma16(dv[f & 1], av[f], b[10 + (f >> 1)][2 * (f & 1)], b[10 + (f >> 1)][2 * (f & 1) + 1]);
                    }
                    sts128f(l16 + C_VP + warp * 512, (dv[0][0] + dv[1][0]) * isc, (dv[0][1] + dv[1][1]) * isc, (dv[0][2] + dv[1][2]) * isc, (dv[0][3] + dv[1][3]) * isc);
                    if (warp == 0) PROF(2);
                }
                auto qk_store = [&]() {
                    uint8_t* rec = rec0 + (size_t)s * (NH * REC) + j * R_J;
                    const uint64_t ef = policy_stream();
                    if (elect()) { bulk_s2g_ef(rec + R_Q, sm + C_QX, 4096, ef); bulk_s2g_ef(rec + R_K, sm + C_KX, 4096, ef); BULK_COMMIT(); }
                    __syncwarp();
                };
                auto qk_stored = [&]() { if (elect()) BULK_WAIT(); __syncwarp(); bar_arrive(B_VM, 160); };
                if (warp >= nu || s + 1 == NSEG) {
                    if (s + 1 < NSEG) bar_arrive(B_RED, 384);
                    if (warp == 3) { bar_sync(B_VP, 384); qk_store(); qk_stored(); } else bar_arrive(B_VP, 384);
                    if (warp == 7 && elect()) {
                        if (s >= 2 && s <= S_NOW) asm volatile("red.relaxed.gpu.global.add.u32 [%0], 1;" :: "l"(&g_flags.seg[(s - 2) * 32 + head]) : "memory");
                        if (s + 3 < NSEG) {
                            const uint8_t* ln = g_acc + ((s + 3) >> 1) * 32768 + ((s + 3) & 1) * 128 + blk * 256;
                            asm volatile("prefetch.global.L2 [%0];" :: "l"(ln) : "memory");
                            if (blk < 4) asm volatile("prefetch.global.L2 [%0];" :: "l"(ln + 96 * 256) : "memory");
                        }
                        if (s + 2 < NSEG && blk < 10) asm volatile("cp.async.bulk.prefetch.L2.global [%0], 4096;" :: "l"(g_h + (s + 2) * SEG * DM + blk * 2048) : "memory");
                    }
                    __syncwarp();
                    if (s + 1 == NSEG) break;
                    mbar_wait(sm + CB_XF, (s + 1) & 1);
                } else {
                    uint32_t w1 = word; PIN(w1); w1 ^= 32;
                    auto frag = [&](int f) { return ((f & 1) ? w1 : word) + (f >> 2) * 14336 + (f >> 1 & 1) * 1024; };
                    uint32_t a[24][4];
                                        uint8_t* acc = g_acc + ((s + 1) >> 1) * 32768 + ((s + 1) & 1) * 128 + (u0 + warp) * 1280;
                    uint32_t ln = l16; PIN(ln); ln = ln >> 4 & 31;
                    uint32_t ox = sm + C_OX + ln * 8;
                    uint8_t* a4 = acc + (ln >> 3) * 256 + (ln & 7) * 16; uint8_t* a1 = acc + 1024 + ln * 4;
                    PIN(ox); PINL(a4); PINL(a1);
                    bar_sync(B_VP, 384);
                    const bool tile = mbar_test(sm + CB_XF, (s + 1) & 1);
                    SFENCE();
#pragma unroll
                    for (int f = 0; f < NW; f++) ldsm4t(a[f], frag(f));
                    if (warp == 3) qk_store();
                    float e[2][4];
                    uint32_t ob[12][2];
                    bar_sync(B_OWN, 128 + 32 * nu);
#pragma unroll
                    for (int k = 0; k < 4; k++) lds64(ob[k], ox + k * 256);
#pragma unroll
                    for (int k = 0; k < 4; k++) {
                        SFENCE();
                        if (k > 0) { ldsm4t(a[2 * k - 2 + NW], frag(2 * k - 2 + NW)); ldsm4t(a[2 * k - 1 + NW], frag(2 * k - 1 + NW)); }
                        if (k == 0) { mma16z(e[0], a[0], ob[0][0], ob[0][1]); mma16z(e[1], a[1], ob[0][0], ob[0][1]); }
                        else { mma16(e[0], a[2 * k], ob[k][0], ob[k][1]); mma16(e[1], a[2 * k + 1], ob[k][0], ob[k][1]); }
                    }
                    SFENCE();
                    ldsm4t(a[6 + NW], frag(6 + NW)); ldsm4t(a[7 + NW], frag(7 + NW));
                    PINL(xo); PINL(xt);
                    if (warp == 3) qk_stored();
                    if (warp == 0) PROF(3);
                    mbar_wait(sm + CB_OX, s & 1);
#pragma unroll
                    for (int k = 4; k < 4 + OD; k++) lds64(ob[k], ox + k * 256);
                    if (warp == 1) PROF(4);
#pragma unroll
                    for (int k = 4; k < 12; k++) {
                        SFENCE();
                        if (k > 4 && k - 1 + OD < 12) lds64(ob[k - 1 + OD], ox + (k - 1 + OD) * 256);
                        if (k > 4 && 2 * k - 2 + NW < 24) { ldsm4t(a[2 * k - 2 + NW], frag(2 * k - 2 + NW)); ldsm4t(a[2 * k - 1 + NW], frag(2 * k - 1 + NW)); }
                        mma16(e[0], a[2 * k], ob[k][0], ob[k][1]); mma16(e[1], a[2 * k + 1], ob[k][0], ob[k][1]);
                    }
                    asm volatile("red.relaxed.gpu.global.add.noftz.v4.f16x2 [%0], {%1,%2,%3,%4};" :: "l"(a4), "r"(packh(e[0][0], e[0][1])), "r"(packh(e[0][2], e[0][3])),
                                 "r"(packh(e[1][0], e[1][1])), "r"(packh(e[1][2], 1.f)) : "memory");
                    asm volatile("red.relaxed.gpu.global.add.noftz.f16x2 [%0], %1;" :: "l"(a1), "r"(packh(e[1][3], 1.f)) : "memory");
                    bar_arrive(B_RED, 384);
                    if (warp == 0) { PROF(5); PROFG(25); }
                    if (!tile) mbar_wait(sm + CB_XF, (s + 1) & 1);
                }
            }
            x_part(s + 1, xo, xt, true, trace);
            start();
            s++;
        }
    } else {
        asm volatile("setmaxnreg.dec.sync.aligned.u32 56;");
        const uint32_t l16 = opaque(sm + lane * 16);
        if (w == 3) {
            const uint64_t ef = policy_stream();
            int c = 0;
#pragma unroll 1
            for (int d = 0; d < 21; d++) {
#pragma unroll 1
                for (; c < 21 && c - d < (d < ar.P[1] ? ar.P[0] : ar.P[2]); c++) {
                    if (c == 10) bar_sync(B_OWN, 160);
                    if (c == 15) bar_sync(B_VM, 160);
                    const uint32_t pb = sm + CB_PC + 8 * (c & 3);
                    if (elect()) {
                        mbar_expect(pb, c < 15 ? 16384 : 14336);
                        if (c < 10) tma2d_ef(sm + C_WV + c * 16384, c < 5 ? &mp.wq : &mp.wk, col0, c % 5 * 128, pb, ef);
                        else if (c < 15) tma2d(sm + C_WV + (c - 10) * 16384, &mp.wv, col0, (c - 10) * 128, pb);
                        else tma3d(sm + C_WO + (c - 15) * 14336, &mp.wo, head * DH + (c - 15 + 2 * j) % 6 * 32, u0, pb);
                    }
                    __syncwarp();
                }
                mbar_wait(sm + CB_PC + 8 * (d & 3), (d >> 2) & 1);
                if ((d == 4 || d == 9 || d == 20) && elect()) mbar_arrive(sm + (d == 4 ? CB_W : d == 9 ? CB_WK : CB_W2));
                __syncwarp();
            }
        } else if (w == 2) {
            if (elect()) {
                flag_add(&g_flags.h);
                PPROF2(12);
                flag_wait(&g_flags.h, 96);
                PPROF2(4);
                h_fetch_a(mp, sm, 0); h_fetch_b(mp, sm, 0);
                flags_release();
                flag_wait(&g_flags.v[head], 2);
                PPROF2(13);
                mbar_expect(sm + CB_VX, 4096);
                bulk_g2s(sm + C_VX, rec0 + j * 4096, 4096, sm + CB_VX);
            }
            __syncwarp();
            if (lane < 16 && blk < 80) g_modt[blk * 16 + lane] = 0;
        }
        uint32_t mx = 0;
#pragma unroll 1
        for (int i = 0; i < 5; i++) { uint32_t v[4]; lds128(v, l16 + C_MEM + (w * 5 + i) * 512); mx = absmax2(absmax2(absmax2(absmax2(mx, v[0]), v[1]), v[2]), v[3]); }
        sts32(sm + C_SCL, 0x3f800000u);
        auto finish = [&](int s) {
            bar_sync(B_VM, 160);
            if (elect()) {
                if (s + 1 < NSEG) h_fetch_b(mp, sm, s + 1);
                bulk_s2g_ef(rec0 + (size_t)s * (NH * REC) + j * R_J + R_KM, sm + C_KM, 2048, policy_stream()); BULK_COMMIT(); BULK_WAIT();
                if (s >= S_NOW) flag_add(&g_flags.seg[s * 32 + head]);
                if (s == S_NOW) asm volatile("red.relaxed.gpu.global.add.u32 [%0], 1;" :: "l"(&g_flags.seg[(s - 1) * 32 + head]) : "memory");
            }
            __syncwarp();
        };
        int ex = 0;
        bool chk = false;
        int nslow = 0;
        uint32_t vb[2][4];
        { const uint32_t vxrd = l16 + lane * 112 + (((2 * w) ^ vswz(lane)) << 4); mbar_wait(sm + CB_VX, 0); ldsm4t(vb[0], vxrd + C_VX); ldsm4t(vb[1], (vxrd ^ 16) + C_VX); }
        bar_sync(B_MEM, 384);
        for (int s = 0; s < NSEG; s++) {
            uint32_t lq = l16; PIN(lq);
            const uint32_t l0 = lq >> 4 & 31, r0 = l0 & 7, m0 = l0 >> 3;
            uint32_t kb[2][4];
            const uint32_t kxrd = sm + C_KX + l0 * 64 + ((w ^ (r0 >> 1)) << 4);
            ldsm4t(kb[0], kxrd); ldsm4t(kb[1], kxrd + 2048);
            if (w == 0 && s + 1 < NSEG && elect()) {
                h_fetch_a(mp, sm, s + 1);
                mbar_expect(sm + CB_VX, 4096);
                bulk_g2s(sm + C_VX, rec0 + (size_t)(s + 1) * (NH * REC) + j * 4096, 4096, sm + CB_VX);
            }
            __syncwarp();
            const uint32_t r1 = (1 - 3 * (j >> 1)) << 24, r2 = (2 - 3 * ((j + 1) >> 1)) << 24;
            uint32_t qrd = sm + C_QM + ((m0 >> 1) + 2 * (m0 & 1)) * 128 + r0 * 16, scdst = sm + C_SC + j * 640 + w * 128 + ((l0 * 4) ^ (w * 32)),
                     sc1 = scdst + r1, sc2 = scdst + r2;
            PIN(qrd); PIN(scdst); PIN(sc1); PIN(sc2);
            for (;;) {
                sts32(sm + C_MAX + w * 4, __reduce_max_sync(0xffffffffu, max(mx & 0xffffu, mx >> 16)) >> 7);
                bar_sync(B_AUX, 128);
                uint32_t m4[4]; lds128(m4, sm + C_MAX);
                const int m = __shfl_sync(0xffffffffu, max(max(m4[0], m4[1]), max(m4[2], m4[3])), 0);
                const bool bad = chk && (m == 255 || m < 127 - 6 || ar.force);
                ex = min(max(ex + 130 - m, -40), 40);
                sts32(sm + C_BAD, bad);
                if (!bad) break;
                bar_sync(B_QK, 384);
                bar_sync(B_RED, 384);
                nslow++;
                if (w == 0 && elect()) {
                    asm volatile("red.release.gpu.global.add.u32 [%0], 1;" :: "l"(&g_flags.slow) : "memory");
                    for (int n = 0;; n++) {
                        uint32_t v; asm volatile("ld.acquire.gpu.global.u32 %0, [%1];" : "=r"(v) : "l"(&g_flags.slow) : "memory");
                        if (v >= 96u * nslow) break;
                        if (n > (1 << 23)) __trap();
                    }
                }
                bar_sync(B_AUX, 128);
                mx = 0;
#pragma unroll 1
                for (int i = 0; i < 10; i++) {
                    float4 a = make_float4(0, 0, 0, 0);
#pragma unroll 4
                    for (int h = 0; h < NH; h++) {
                        const float4 v = __ldcg((const float4*)(g_slow + ((((s & 1) * NH + h) * 20 + w * 5 + (i >> 1)) * 32 + l0) * 8) + (i & 1));
                        a.x += v.x; a.y += v.y; a.z += v.z; a.w += v.w;
                    }
                    const uint32_t o0 = pack2(a.x, a.y), o1 = pack2(a.z, a.w);
                    sts32(sm + C_MEM + (w * 10 + i) * 256 + l0 * 4, o0); sts32(sm + C_MEM + (w * 10 + i) * 256 + 128 + l0 * 4, o1);
                    mx = absmax2(absmax2(mx, o0), o1);
                }
                sts32(sm + C_SCL, 0x3f800000u);
                ex = 0; chk = false;
                bar_sync(B_MEM, 384);
            }
            if (s + 1 == NSEG) {
                bar_sync(B_QK, 384);
                bar_sync(B_VP, 384);
                const float4 y0 = lds128f(lq + C_VP + w * 512), y1 = lds128f(lq + C_VP + w * 512 + 2048);
                sts32(sm + C_VM + w * 256 + l0 * 4, pack2(y0.x + y1.x, y0.y + y1.y)); sts32(sm + C_VM + w * 256 + 128 + l0 * 4, pack2(y0.z + y1.z, y0.w + y1.w));
                PROXY_FENCE();
                if (w == 2) { finish(s); if (elect()) PPROF2(15); } else bar_arrive(B_VM, 160);
                break;
            }
            if (w == 3) {
                uint32_t qa[2][4], km[2][4], x, y;
                bar_sync(B_QK, 384);
                ldsm4t(qa[0], qrd); ldsm4t(km[0], lq + C_KM); ldsm4t(qa[1], qrd + 512); ldsm4t(km[1], lq + C_KM + 512);
                SFENCE();
                score_tiles(qa, kb, km, x, y);
                stas1(sc1, x, sm + CB_SC + r1); stas1(sc2, x, sm + CB_SC + r2); stas1(sc1 + 128, y, sm + CB_SC + r1); stas1(sc2 + 128, y, sm + CB_SC + r2);
                sts32(scdst, x); sts32(scdst + 128, y);
            } else {
                uint32_t qa[2][4];
                bar_sync(B_QK, 384);
                ldsm4t(qa[0], qrd); ldsm4t(qa[1], qrd + 512);
                if (w == 0) PROF(6);
                const uint32_t x = score_tile(qa, kb);
                stas1(sc1, x, sm + CB_SC + r1); stas1(sc2, x, sm + CB_SC + r2);
                sts32(scdst, x);
            }
            __syncwarp();
            if (elect()) mbar_arrive(sm + CB_SC);
            SFENCE();
            if (w == 0) PROF(7);
            uint32_t scrd = sm + C_SC + (l0 & 3) * 128 + (((l0 >> 2) ^ (2 * (l0 & 3))) << 4), zrd = sm + C_SC + 512 + ((l0 * 4) ^ 96),
                     od = sm + C_OX + l0 * 8 + w * 256, od1 = od + r1 + 2048, od2 = od + r2 + 1024, vprd = lq + C_VP + w * 512, vmst = sm + C_VM + w * 256 + l0 * 4, ones = 0x3f803f80u, ones2 = 0x3f803f80u, zero = 0;
            PIN(scrd); PIN(zrd); PIN(od); PIN(od1); PIN(od2); PIN(vprd); PIN(vmst); PIN(ones); PIN(ones2); PIN(zero);
            mbar_wait(sm + CB_SC, s & 1);
            float sv[10];
            {
                uint32_t x[3][4], z[3];
#pragma unroll
                for (int p = 0; p < 3; p++) { lds128(x[p], scrd + p * 640); z[p] = lds32(zrd + p * 640); }
                if (w == 1) PROF(8);
#pragma unroll
                for (int i = 0; i < 4; i++) { sv[2 * i] = (lo_f(x[0][i]) + lo_f(x[1][i])) + lo_f(x[2][i]); sv[2 * i + 1] = (hi_f(x[0][i]) + hi_f(x[1][i])) + hi_f(x[2][i]); }
                sv[8] = (lo_f(z[0]) + lo_f(z[1])) + lo_f(z[2]); sv[9] = (hi_f(z[0]) + hi_f(z[1])) + hi_f(z[2]);
            }
            float mxs = fmaxf(fmaxf(fmaxf(sv[0], sv[1]), fmaxf(sv[2], sv[3])), fmaxf(fmaxf(fmaxf(sv[4], sv[5]), fmaxf(sv[6], sv[7])), fmaxf(sv[8], sv[9])));
            {
                const float a = __shfl_xor_sync(0xffffffffu, mxs, 1), b = __shfl_xor_sync(0xffffffffu, mxs, 2), c = __shfl_xor_sync(0xffffffffu, mxs, 3);
                mxs = fmaxf(fmaxf(mxs, a), fmaxf(b, c));
            }
#pragma unroll
            for (int i = 0; i < VPB; i++) sv[i] = ex2(sv[i] - mxs);
            SFENCE();
            bar_sync(B_VP, 384);
            const float4 y0 = lds128f(vprd), y1 = lds128f(vprd + 2048);
            SFENCE();
#pragma unroll
            for (int i = VPB; i < 10; i++) sv[i] = ex2(sv[i] - mxs);
            const uint32_t pa[4] = {pack2(sv[0], sv[1]), pack2(sv[4], sv[5]), pack2(sv[2], sv[3]), pack2(sv[6], sv[7])}, pm = pack2(sv[8], sv[9]);
            if (w == 2) PROF(9);
            {
                float o[2][4], o2[2][4], om[2][4], sx[4], sy[4];
                mma16z(sx, pa, ones, ones2);
                mma16z(o[0], pa, vb[0][0], vb[0][1]); mma16z(o2[0], pa, vb[0][2], vb[0][3]);
                mma8z(sy, pm, zero, ones);
                mma16z(o[1], pa, vb[1][0], vb[1][1]); mma16z(o2[1], pa, vb[1][2], vb[1][3]);
                SFENCE();
                const uint32_t vm0 = pack2(y0.x + y1.x, y0.y + y1.y), vm1 = pack2(y0.z + y1.z, y0.w + y1.w);
                mma8z(om[0], pm, zero, vm0); mma8z(om[1], pm, zero, vm1);
                float inv; asm("rcp.approx.ftz.f32 %0, %1;" : "=f"(inv) : "f"((sx[0] + sx[2]) + sy[0]));
                inv *= __int_as_float((127 + ex) << 23);
                const uint32_t a = pack2(((o[0][0] + o2[0][2]) + om[0][0]) * inv, ((o[0][1] + o2[0][3]) + om[0][1]) * inv),
                               b = pack2(((o[1][0] + o2[1][2]) + om[1][0]) * inv, ((o[1][1] + o2[1][3]) + om[1][1]) * inv);
                stas2(od1, a, b, sm + CB_OX + r1); stas2(od2, a, b, sm + CB_OX + r2);
                asm volatile("st.shared.v2.b32 [%0], {%1,%2};" :: "r"(od), "r"(a), "r"(b) : "memory");
                bar_arrive(B_OWN, 128 + 32 * nu);
                sts32(vmst, vm0); sts32(vmst + 128, vm1);
                PROXY_FENCE();
                if (w != 2) bar_arrive(B_VM, 160);
                if (w == 0) PROF(10);
            }
            const uint8_t* acc = g_acc + ((s + 1) >> 1) * 32768 + ((s + 1) & 1) * 128 + w * 1280;
            const uint8_t* a4 = acc + (l0 >> 3) * 256 + (l0 & 7) * 16; const uint8_t* a1 = acc + 1024 + l0 * 4;
            PINL(a4); PINL(a1);
            const uint32_t* vf = &g_flags.v[(min(s + 2, NSEG - 1) >> 2) * 32 + head];
            uint32_t vok = 2;
            if (w == 0 && (s & 3) == 2) vok = ld_rlx(vf);
            if (w == 1 && elect()) { mbar_expect(sm + CB_SC, 1280); sts32(sm + C_SCL, (127 - ex) << 23); }
            __syncwarp();
            uint32_t tw;
            if (w == 2) {
                bar_arrive(B_RED, 384);
                finish(s);
                bar_sync(B_T, 64);
                tw = lds32(sm + C_TW);
            } else {
                bar_sync(B_RED, 384);
                SFENCE();
                tw = clock();
                SFENCE();
                if (w == 3) { sts32(sm + C_TW, tw); bar_arrive(B_T, 64); }
            }
            if (w == 1 && elect()) mbar_expect(sm + CB_OX, 2048);
            __syncwarp();
            { const uint32_t vxrd = lq + l0 * 112 + (((2 * w) ^ vswz(l0)) << 4); mbar_wait(sm + CB_VX, (s + 1) & 1); ldsm4t(vb[0], vxrd + C_VX); ldsm4t(vb[1], (vxrd ^ 16) + C_VX); }
            if (__any_sync(0xffffffffu, vok < 2)) flag_wait_warp(vf, 2);
            wait_until(tw + ar.D + (j == 2 ? ar.D2 : 0));
            if (w == 2) PROF(16);
            uint32_t v[5][4], z[5];
            int n = 0;
#pragma unroll
            for (int i = 0; i < 5; i++) {
                asm volatile("ld.relaxed.gpu.global.v4.u32 {%0,%1,%2,%3}, [%4];" : "=r"(v[i][0]), "=r"(v[i][1]), "=r"(v[i][2]), "=r"(v[i][3]) : "l"(a4 + (4 - i) * 5120) : "memory");
                asm volatile("ld.relaxed.gpu.global.u32 %0, [%1];" : "=r"(z[i]) : "l"(a1 + (4 - i) * 5120) : "memory");
            }
            while (__any_sync(0xffffffffu, min(min(min(v[0][3], z[0]), min(v[1][3], z[1])), min(min(min(v[2][3], z[2]), min(v[3][3], z[3])), min(v[4][3], z[4]))) < 0x50000000u)) {
#pragma unroll
                for (int i = 0; i < 5; i++) {
                    asm volatile("{ .reg .pred q; setp.lt.u32 q, %3, 0x50000000;\n@q ld.relaxed.gpu.global.v4.u32 {%0,%1,%2,%3}, [%4]; }" : "+r"(v[i][0]), "+r"(v[i][1]), "+r"(v[i][2]), "+r"(v[i][3]) : "l"(a4 + (4 - i) * 5120) : "memory");
                    asm volatile("{ .reg .pred q; setp.lt.u32 q, %0, 0x50000000;\n@q ld.relaxed.gpu.global.u32 %0, [%1]; }" : "+r"(z[i]) : "l"(a1 + (4 - i) * 5120) : "memory");
                }
                if (++n > SPIN_LIMIT) __trap();
            }
            if (w == 0) { PROF(11); PROFV(15, n); }
#pragma unroll
            for (int i = 0; i < 5; i++) {
                v[i][0] = h2b(v[i][0]); v[i][1] = h2b(v[i][1]); v[i][2] = h2b(v[i][2]); v[i][3] = h2b_lo(v[i][3], z[i]);
                stsm4(lq + C_MEM + w * 512 + (4 - i) * 2048, v[i][0], v[i][1], v[i][2], v[i][3]);
            }
            bar_sync(B_MEM, 384);
            SFENCE();
            mx = 0;
#pragma unroll
            for (int i = 0; i < 5; i++) mx = absmax2(absmax2(absmax2(absmax2(mx, v[i][0]), v[i][1]), v[i][2]), v[i][3]);
            chk = true;
        }
    }
}

struct SideMaps { CUtensorMap h, wv, ost, o, o64, wo, slab3, slab2, ln[3], wgate, wup, wdown; };
constexpr int NRUN = 48;
struct Sched { uint16_t end[NRUN + 1]; uint8_t kind[NRUN + 1], block[NRUN + 1], lsplit[16], slab[16]; int bgrows; };
constexpr int SD_SL = REC / 3, SD_NSL = 12, SD_EPI = SD_NSL * SD_SL, SD_VEC = SD_EPI + 2 * 24576, SD_BAR = SD_VEC + 6400, SD_SMEM = SD_BAR + 768;
static_assert(SD_SMEM <= 232448, "side shared memory");

template <int NPC, bool V>
__device__ __forceinline__ void tile_out(const float (&acc)[8 * NPC], uint32_t eb, uint32_t efull, uint32_t eempty, int& eph, int w, int lane) {
    const int r = lane & 7, mi = lane >> 3, row = w * 16 + (mi & 1) * 8 + r;
    const uint32_t rb = V ? eb + (row >> 5) * 12288 + (row & 31) * 128 : eb + row * 128, sw = V ? vswz(row & 31) : r;
    mbar_wait(eempty, eph); eph ^= 1;
#pragma unroll
    for (int p = 0; p < NPC; p++) {
        const int oc = 2 * p + (mi >> 1);
        stsm4(rb + (oc >> 3) * (V ? 4096 : 8192) + (((oc & 7) ^ sw) << 4), pack2(acc[8 * p], acc[8 * p + 1]), pack2(acc[8 * p + 2], acc[8 * p + 3]),
              pack2(acc[8 * p + 4], acc[8 * p + 5]), pack2(acc[8 * p + 6], acc[8 * p + 7]));
    }
    PROXY_FENCE();
    __syncwarp();
    if (lane == 0) mbar_arrive(efull);
}

__device__ __forceinline__ void arrive_after(uint32_t bar, uint32_t zero, uint32_t a, uint32_t b, uint32_t c, uint32_t d, int lane) {
    if (lane == 0) mbar_arrive(bar + ((a | b | c | d) & zero));
}
__device__ __forceinline__ uint32_t bmax(uint32_t a, uint32_t b) { uint32_t r; asm("max.bf16x2 %0, %1, %2;" : "=r"(r) : "r"(a), "r"(b)); return r; }
__device__ __forceinline__ void attn_units(uint32_t base, uint32_t dst, uint32_t bars, int mt, int lane) {
    const uint32_t FQ = bars, FV = bars + 8, EQ = bars + 16, PD = bars + 24, SE = bars + 32, EV = bars + 40, STOP = bars + 48;
    const int r = lane & 7, mi = lane >> 3, g = lane >> 2, t = lane & 3;
    const uint32_t tok = 8 * (r >> 1) + 2 * mi + (r & 1);
    const uint32_t qrd = opaque(base + R_Q + ((mi >> 1) * 8 + r) * 64 + (((2 * mt + (mi & 1)) ^ (r >> 1)) << 4)), mrd = opaque(base + lane * 16), zero = opaque(lane >> 5);
    uint32_t krd[4], vrd[8], ost[4], vis[2][4];
#pragma unroll
    for (int n = 0; n < 4; n++) {
        krd[n] = opaque(base + R_K + lane * 64 + ((n ^ (r >> 1)) << 4));
        ost[n] = opaque(dst + ((mi & 1) * 8 + r) * 128 + (((2 * n + (mi >> 1)) ^ r) << 4));
#pragma unroll
        for (int hf = 0; hf < 2; hf++) {
            const int lim = 8 * (g >> 1) + 2 * (2 * mt + hf) + (g & 1) - 8 * t - 2 * n;
            vis[hf][n] = opaque(lim < 0 ? 0u : lim < 1 ? 0xffffu : ~0u);
        }
    }
#pragma unroll
    for (int u = 0; u < 8; u++) vrd[u] = opaque(base + tok * 128 + ((u ^ vswz(tok)) << 4));
    const float scale = 0.07216878364870322f, l2e = 1.4426950408889634f;
#pragma unroll 1
    for (int ph = 0;; ph ^= 1) {
        mbar_wait(FQ, ph);
        float sc[5][4];
        uint32_t a[6][2][4], bb[6][5][4], bm[6][4];
        auto load = [&](int k2) {
            const uint32_t cb = (k2 >> 1) * R_J + (k2 & 1) * 2048;
            ldsm4t(a[k2][0], qrd + cb);
#pragma unroll
            for (int n = 0; n < 4; n++) ldsm4t(bb[k2][n], krd[n] + cb);
            ldsm4t(bb[k2][4], mrd + R_KM + (k2 >> 1) * R_J + (k2 & 1) * 512);
            ldsm4t(a[k2][1], qrd + cb + 1024);
        };
        const uint32_t stop = lds32(STOP);
        load(0); load(1);
        if (stop) break;
#pragma unroll
        for (int k2 = 0; k2 < 6; k2++) {
            SFENCE();
            if (k2 + 2 < 6) load(k2 + 2);
            else {
#pragma unroll
                for (int n = 0; n < 3; n++) { const int n4 = 3 * (k2 - 4) + n; ldsm4(bm[n4], mrd + R_VM + (n4 >> 1) * R_J + (n4 & 1) * 512); }
            }
#pragma unroll
            for (int n = 0; n < 5; n++) { if (k2 == 0) mma16z(sc[n], a[k2][0], bb[k2][n][0], bb[k2][n][1]); else mma16(sc[n], a[k2][0], bb[k2][n][0], bb[k2][n][1]); }
#pragma unroll
            for (int n = 0; n < 5; n++) mma16(sc[n], a[k2][1], bb[k2][n][2], bb[k2][n][3]);
        }
        uint32_t vb[6][4][4];
        auto vload = [&](int n4) {
#pragma unroll
            for (int u = 0; u < 4; u++) ldsm4t(vb[n4][u], vrd[(n4 & 1) * 4 + u] + (n4 >> 1) * 4096);
        };
        uint32_t sv[2][5], mx[2];
#pragma unroll
        for (int hf = 0; hf < 2; hf++) {
#pragma unroll
            for (int n = 0; n < 5; n++) {
                uint32_t u = pack2(sc[n][2 * hf], sc[n][2 * hf + 1]);
                u = pack2(lo_f(u) * scale, hi_f(u) * scale);
                sv[hf][n] = n < 4 ? (u & vis[hf][n & 3]) | (0xce6ece6eu & ~vis[hf][n & 3]) : u;
            }
            mx[hf] = bmax(bmax(bmax(sv[hf][0], sv[hf][1]), bmax(sv[hf][2], sv[hf][3])), sv[hf][4]);
        }
        arrive_after(EQ, zero, bm[0][0] | bm[1][0], bm[2][0] | bm[3][0], bm[4][0], bm[5][0], lane);
        uint32_t m2 = bmax(__byte_perm(mx[0], mx[1], 0x5410), __byte_perm(mx[0], mx[1], 0x7632));
        m2 = bmax(bmax(m2, __shfl_xor_sync(0xffffffffu, m2, 1)), bmax(__shfl_xor_sync(0xffffffffu, m2, 2), __shfl_xor_sync(0xffffffffu, m2, 3)));
        float v[2][10], sum[2];
#pragma unroll
        for (int hf = 0; hf < 2; hf++) {
            const float m = hf ? hi_f(m2) : lo_f(m2);
#pragma unroll
            for (int q = 0; q < 10; q++) asm("ex2.approx.ftz.f32 %0, %1;" : "=f"(v[hf][q]) : "f"(((q & 1 ? hi_f(sv[hf][q >> 1]) : lo_f(sv[hf][q >> 1])) - m) * l2e));
            sum[hf] = (((v[hf][0] + v[hf][1]) + (v[hf][2] + v[hf][3])) + ((v[hf][4] + v[hf][5]) + (v[hf][6] + v[hf][7]))) + (v[hf][8] + v[hf][9]);
        }
#pragma unroll
        for (int o = 1; o < 4; o <<= 1)
#pragma unroll
            for (int hf = 0; hf < 2; hf++) sum[hf] += __shfl_xor_sync(0xffffffffu, sum[hf], o);
        mbar_wait(FV, ph);
        vload(0); vload(1); vload(2); vload(3);
        SFENCE();
        uint32_t pa[2][4], pm[2];
#pragma unroll
        for (int hf = 0; hf < 2; hf++) {
            float inv; asm("rcp.approx.ftz.f32 %0, %1;" : "=f"(inv) : "f"(sum[hf]));
#pragma unroll
            for (int n = 0; n < 4; n++) pa[n >> 1][2 * (n & 1) + hf] = pack2(v[hf][2 * n] * inv, v[hf][2 * n + 1] * inv);
            pm[hf] = pack2(v[hf][8] * inv, v[hf][9] * inv);
        }
        mbar_wait(SE, ph ^ 1);
        float o[6][4][4];
#pragma unroll
        for (int n4 = 0; n4 < 7; n4++) {
            SFENCE();
            if (n4 == 1 || n4 == 2) vload(n4 + 3);
            if (n4 == 4) arrive_after(EV, zero, vb[4][0][0] | vb[5][0][0], vb[4][1][0] | vb[5][1][0], vb[4][2][0] | vb[5][2][0], vb[4][3][0] | vb[5][3][0], lane);
            if (n4 < 6) {
#pragma unroll
                for (int u = 0; u < 4; u++) mma8z(o[n4][u], pm[0], pm[1], bm[n4][u]);
#pragma unroll
                for (int h = 0; h < 2; h++)
#pragma unroll
                    for (int u = 0; u < 4; u++) mma16(o[n4][u], pa[h], vb[n4][u][2 * h], vb[n4][u][2 * h + 1]);
            }
            if (n4 > 0) {
#pragma unroll
                for (int p = 0; p < 2; p++) {
                    const float (&x)[4] = o[n4 - 1][2 * p], (&y)[4] = o[n4 - 1][2 * p + 1];
                    stsm4(ost[((n4 - 1) & 1) * 2 + p] + ((n4 - 1) >> 1) * 4096, pack2(x[0], x[1]), pack2(x[2], x[3]), pack2(y[0], y[1]), pack2(y[2], y[3]));
                }
            }
        }
        PROXY_FENCE();
        __syncwarp();
        if (lane == 0) mbar_arrive(PD);
    }
}

__device__ __forceinline__ void ln2_row(const uint32_t (&av)[5][2], const uint2 (&xn)[5], int row, uint32_t vec, bf16* out, uint64_t ef, int lane) {
    uint32_t xv[10], hv[10];
#pragma unroll
    for (int q2 = 0; q2 < 5; q2++) {
        uint32_t ga[2]; lds64(ga, vec + q2 * 256);
        xv[2 * q2] = badd(xn[q2].x, bmul(ga[0], av[q2][0]));
        xv[2 * q2 + 1] = badd(xn[q2].y, bmul(ga[1], av[q2][1]));
    }
    ln_row(xv, hv);
    float r0 = 0, r1 = 0;
#pragma unroll
    for (int q2 = 0; q2 < 5; q2++) {
        const int c = row * DM + lane * 4 + q2 * 128;
        uint32_t sh[2], sc[2], gb[2], wv[2];
        lds64(sh, vec + 1280 + q2 * 256); lds64(sc, vec + 2560 + q2 * 256); lds64(gb, vec + 3840 + q2 * 256); lds64(wv, vec + 5120 + q2 * 256);
        const uint32_t h0 = badd(bmul(hv[2 * q2], badd(sc[0], 0x3f803f80u)), sh[0]), h1 = badd(bmul(hv[2 * q2 + 1], badd(sc[1], 0x3f803f80u)), sh[1]);
        r0 += lo_f(h0) * lo_f(wv[0]) + hi_f(h0) * hi_f(wv[0]); r1 += lo_f(h1) * lo_f(wv[1]) + hi_f(h1) * hi_f(wv[1]);
        st_ef(g_h2 + c, make_uint2(h0, h1), ef);
        st_ef(g_x1 + c, make_uint2(xv[2 * q2], xv[2 * q2 + 1]), ef);
        st_ef(out + c, make_uint2(badd(xv[2 * q2], bmul(gb[0], h0)), badd(xv[2 * q2 + 1], bmul(gb[1], h1))), ef);
    }
    const float rsum = warp_sum(r0 + r1);
    if (lane == 0) g_r[row] = __float2bfloat16_rn(rsum);
}
__device__ __forceinline__ int pos_row(int pos) { return (pos & ~31) + 8 * ((pos & 7) >> 1) + 2 * ((pos >> 3) & 3) + (pos & 1); }
__device__ __forceinline__ uint32_t claim(uint32_t* ctr) {
    uint32_t v; asm volatile("{ .reg .pred e; elect.sync _|e, -1; mov.u32 %0, 0; @e atom.relaxed.gpu.global.add.u32 %0, [%1], 1; }" : "=r"(v) : "l"(ctr) : "memory"); return v;
}
__device__ __forceinline__ void flag_wait_idle(const uint32_t* f, uint32_t target) {
    for (int n = 0; !__all_sync(0xffffffffu, ld_rlx(f) >= target); n++) { __nanosleep(400); if (n > (1 << 20)) __trap(); }
}
#define APROF(u)
__device__ __forceinline__ uint32_t lds_acq(uint32_t a) { uint32_t v; asm volatile("ld.acquire.cta.shared.u32 %0, [%1];" : "=r"(v) : "r"(a) : "memory"); return v; }
__device__ __forceinline__ void attn_manager(const SideMaps& mp, uint32_t base, uint32_t stg, uint32_t bars, uint32_t post, const bf16* x, uint64_t ef) {
    const uint32_t FQ = bars, FV = bars + 8, EQ = bars + 16, PD = bars + 24, SE = bars + 32, EV = bars + 40, STOP = bars + 48;
    int ph = 0, np = 0, prev = -1, pend = -1;
    auto flush = [&]() {
        if (pend >= 0 && elect()) {
            BULK_WAIT(); mbar_arrive(SE);
            const uint32_t slot = post + (np & 3) * 4;
            for (int n = 0; lds_acq(slot); n++) if (n > (1 << 22)) __trap();
            asm volatile("st.release.cta.shared.u32 [%0], %1;" :: "r"(slot), "r"(pend + 1) : "memory");
        }
        np += pend >= 0;
        pend = -1; __syncwarp();
    };
    auto store = [&]() {
        mbar_wait(PD, ph ^ 1);
        if (elect()) { tma3d_store(&mp.ost, prev & ~31, (prev & 31) * 3, stg, ef, false); BULK_COMMIT(); }
        pend = prev; prev = -1;
    };
    int u = __reduce_max_sync(0xffffffffu, claim(&g_flags.anext));
    uint32_t fl = 0;
#pragma unroll 1
    for (;;) {
        if (u >= NSEG * NH) { flush(); if (prev >= 0) { store(); flush(); } break; }
        if (!__all_sync(0xffffffffu, fl >= 3)) {
            flush();
#pragma unroll 1
            for (int n = 0; !__all_sync(0xffffffffu, ld_rlx(&g_flags.seg[u]) >= 3); n++) {
                if (prev >= 0 && mbar_test(PD, ph ^ 1)) { store(); flush(); }
                if (NAP) __nanosleep(NAP);
                if (n > (1 << 23)) __trap();
            }
        }
        const uint8_t* rec = g_rec + (size_t)u * REC;
        const uint32_t nxt = claim(&g_flags.anext);
        mbar_wait(EQ, ph ^ 1);
        if (elect()) { mbar_expect(FQ, REC - R_Q); bulk_g2s_ef(base + R_Q, rec + R_Q, REC - R_Q, FQ, ef); APROF(2048 + u); }
        const int un = __reduce_max_sync(0xffffffffu, nxt);
        fl = ld_rlx(&g_flags.seg[min(un, NSEG * NH - 1)]);
        flush();
        mbar_wait(EV, ph ^ 1);
        if (elect()) {
            mbar_expect(FV, R_Q); bulk_g2s_ef(base, rec, R_Q, FV, ef);
            asm volatile("cp.async.bulk.prefetch.L2.global [%0], 1280;" :: "l"(x + u * DM) : "memory");
        }
        if (prev >= 0) store();
        prev = u; ph ^= 1; u = un;
    }
    if (elect()) { sts32(STOP, 1); mbar_arrive(FQ); }
    __syncwarp();
}

#define SPROF(tk, i)
#define FWAIT(bar, par) mbar_wait(bar, par)
#define EPROF()
#define TPROF(i)
__device__ __forceinline__ void side_tail(uint32_t wgu, uint32_t wgu_bar, int wgu_ph, uint32_t wd, uint32_t wd_bar, int wd_ph, uint32_t xb, uint32_t gbar, bf16* out, int tid) {
    const int warp = __shfl_sync(0xffffffffu, tid >> 5, 0), lane = tid & 31, r = lane & 7, mi = lane >> 3, blk = blockIdx.x;
    const uint32_t T_GU = xb, T_X = xb + 24576, T_RED = T_X + 10240, T_KEY = T_RED + 8192;
    TPROF(0);
    auto rkey = [](int idx) { uint32_t u = __ldcg((const unsigned short*)g_r + idx); u = (u & 0x8000u) ? (~u & 0xffffu) : (u | 0x8000u); return (u << 16) | (uint32_t)(S_TOK - 1 - idx); };
    {
        if (warp == 0 && lane < 15) flag_wait(&g_flags.ln[lane * 32], 128);
        bar_sync(1, 256);
        uint32_t k[8];
#pragma unroll
        for (int i = 0; i < 8; i++) { const int idx = warp * 240 + i * 32 + lane; k[i] = i * 32 + lane < 240 ? rkey(idx) : 0u; }
#pragma unroll 1
        for (int it = 0; it < 8; it++) {
            const uint32_t m = __reduce_max_sync(0xffffffffu, max(umax3(k[0], k[1], k[2]), max(umax3(k[3], k[4], k[5]), max(k[6], k[7]))));
#pragma unroll
            for (int i = 0; i < 8; i++) if (k[i] == m) k[i] = 0;
            if (lane == 0) sts32(T_KEY + (warp * 8 + it) * 4, m);
        }
    }
    bar_sync(1, 256);
    if (warp == 0) {
        uint32_t k[6];
        k[0] = lds32(T_KEY + lane * 4); k[1] = lds32(T_KEY + 128 + lane * 4);
        if (lane == 0) flag_wait(&g_flags.ln[15 * 32], 128);
        __syncwarp();
        TPROF(1);
        if (blk == 40 && lane == 0) LPROF(3);
#pragma unroll
        for (int i = 0; i < 4; i++) k[2 + i] = rkey(1920 + i * 32 + lane);
#pragma unroll 1
        for (int it = 0; it < 8; it++) {
            const uint32_t m = __reduce_max_sync(0xffffffffu, max(umax3(k[0], k[1], k[2]), umax3(k[3], k[4], k[5])));
#pragma unroll
            for (int i = 0; i < 6; i++) if (k[i] == m) k[i] = 0;
            if (lane == 0) sts32(T_KEY + 256 + it * 4, S_TOK - 1 - (m & 0xffffu));
        }
    }
    bar_sync(1, 256);
    TPROF(2);
    {
        const bf16* src = g_h2 + lds32(T_KEY + 256 + (tid & 7) * 4) * DM + (tid >> 3) * 8;
        uint4 v[3];
#pragma unroll
        for (int i = 0; i < 3; i++) if (i < 2 || tid < 128) v[i] = __ldcg((const uint4*)(src + i * 256));
#pragma unroll
        for (int i = 0; i < 3; i++) if (i < 2 || tid < 128) sts128(T_X + tid * 16 + i * 4096, v[i].x, v[i].y, v[i].z, v[i].w);
    }
    const int trow = lds32(T_KEY + 256 + (lane >> 2) * 4), tcol = (blk < 80 ? blk : 0) * 8 + (lane & 3) * 2;
    const uint32_t fx1 = __ldcg((const uint32_t*)(g_x1 + trow * DM + tcol)), fh2 = __ldcg((const uint32_t*)(g_h2 + trow * DM + tcol)),
                   fgb = __ldcg((const uint32_t*)(g_mod + 5 * DM + tcol));
    const float fr = __uint_as_float((uint32_t)__ldcg((const unsigned short*)g_r + trow) << 16);
    mbar_wait(wgu_bar, wgu_ph);
    bar_sync(1, 256);
    TPROF(3);
    {
        float dg[4] = {0, 0, 0, 0}, du[4] = {0, 0, 0, 0};
#pragma unroll
        for (int k = 0; k < 5; k++) {
            uint32_t b[4], ag[4], au[4];
            ldsm4(b, T_X + (warp * 5 + k) * 256 + (lane & 15) * 16);
            const uint32_t o = ((warp * 5 + k) * 16 + (mi >> 1) * 8 + r) * 32 + (mi & 1) * 16;
            ldsm4t(ag, wgu + o); ldsm4t(au, wgu + 20480 + o);
            mma16(dg, ag, b[0], b[1]); mma16(du, au, b[0], b[1]);
        }
        sts128f(T_RED + warp * 1024 + lane * 16, dg[0], dg[1], dg[2], dg[3]); sts128f(T_RED + warp * 1024 + 512 + lane * 16, du[0], du[1], du[2], du[3]);
    }
    bar_sync(1, 256);
    if (warp == 0) {
        float g4[4] = {0, 0, 0, 0}, u4[4] = {0, 0, 0, 0};
#pragma unroll
        for (int i = 0; i < 8; i++) {
            const float4 a = lds128f(T_RED + i * 1024 + lane * 16), b = lds128f(T_RED + i * 1024 + 512 + lane * 16);
            g4[0] += a.x; g4[1] += a.y; g4[2] += a.z; g4[3] += a.w; u4[0] += b.x; u4[1] += b.y; u4[2] += b.z; u4[3] += b.w;
        }
        float y[4];
#pragma unroll
        for (int i = 0; i < 4; i++) { const float gq = bfr(g4[i]); y[i] = bfr(__fdividef(gq, 1.f + __expf(-gq))) * bfr(u4[i]); }
        g_gu[blk * 64 + lane] = movm_t(pack2(y[0], y[1])); g_gu[blk * 64 + 32 + lane] = movm_t(pack2(y[2], y[3]));
        __syncwarp();
        TPROF(4);
        if (lane == 0) {
            flag_add(&g_flags.gu);
            if (blk < 80) {
                flag_wait(&g_flags.gu, 96);
                mbar_expect(gbar, 24576); bulk_g2s(T_GU, g_gu, 24576, gbar);
            }
        }
        __syncwarp();
    }
    if (blk < 80) {
        mbar_wait(wd_bar, wd_ph);
        mbar_wait(gbar, 0);
        TPROF(5);
        float d[2][4] = {{0, 0, 0, 0}, {0, 0, 0, 0}};
#pragma unroll
        for (int k2 = 0; k2 < 6; k2++) {
            uint32_t b[4]; ldsm4t(b, wd + (warp * 6 + k2) * 512 + lane * 16);
#pragma unroll
            for (int h = 0; h < 2; h++) {
                uint32_t a[4]; ldsm4(a, T_GU + ((warp * 12 + k2 * 2 + h) * 2 + (mi >> 1)) * 128 + r * 16);
                mma16(d[h], a, b[2 * h], b[2 * h + 1]);
            }
        }
        asm volatile("st.shared.v2.f32 [%0], {%1,%2};" :: "r"(T_X + warp * 256 + lane * 8), "f"(d[0][0] + d[1][0]), "f"(d[0][1] + d[1][1]) : "memory");
        bar_sync(1, 256);
        if (warp == 0) {
            float y0 = 0, y1 = 0;
#pragma unroll
            for (int i = 0; i < 8; i++) { const float2 a = lds64f(T_X + i * 256 + lane * 8); y0 += a.x; y1 += a.y; }
            const float sg = bfr(__fdividef(1.f, 1.f + __expf(-fr)));
            const float b0 = bfr(lo_f(fh2) + bfr(bfr(y0) * sg)), b1 = bfr(hi_f(fh2) + bfr(bfr(y1) * sg));
            *(uint32_t*)(out + trow * DM + tcol) = pack2(lo_f(fx1) + bfr(lo_f(fgb) * b0), hi_f(fx1) + bfr(hi_f(fgb) * b1));
        }
    }
    TPROF(6);
    if (blk == 40 && tid == 0) LPROF(5);
}

__global__ void __launch_bounds__(512, 1) k_side(const __grid_constant__ SideMaps mp, const __grid_constant__ Sched sd, const bf16* __restrict__ x,
                                                 const bf16* __restrict__ wr, const bf16* __restrict__ cin, const bf16* __restrict__ wmod, bf16* __restrict__ out) {
    extern __shared__ __align__(1024) uint8_t smraw[];
    const uint32_t sm = smem_u32(smraw);
    if (sm & 1023) __trap();
    const uint32_t FULL = sm + SD_BAR, EMPTY = FULL + 96, EFULL = FULL + 192, EEMPTY = EFULL + 16, IFULL = EFULL + 32, IEMPTY = EFULL + 64, IQ = EFULL + 96,
                   VEC = EFULL + 112, GBAR = EFULL + 120, LNDONE = EFULL + 128, LNFREE = EFULL + 136, GO = EFULL + 144, MODE = EFULL + 152, POST = FULL + 384, ATT = FULL + 512;
    const int tid = threadIdx.x, warp = __shfl_sync(0xffffffffu, tid >> 5, 0), lane = tid & 31;
    if (blockIdx.x == 0 && tid == 0) LPROF(4);
    if (tid >= 32 && tid < 32 + SD_NSL) { mbar_init(FULL + 8 * (tid - 32), 1); mbar_init(EMPTY + 8 * (tid - 32), 8); asm volatile("fence.mbarrier_init.release.cluster;" ::: "memory"); }
    if (tid >= 64 && tid < 96) {
        const int k = tid & 7;
        if (k < 6) mbar_init(ATT + (tid - 64) * 8, k == 2 || k == 3 || k == 5 ? 2 : 1); else sts32(ATT + (tid - 64) * 8, 0);
        asm volatile("fence.mbarrier_init.release.cluster;" ::: "memory");
    }
    if (tid >= 96 && tid < 128) sts32(POST + lane * 4, 0);
    if (tid == 0) {
        mbar_init(GO, 1); mbar_init(MODE, 1);
        for (int i = 0; i < 2; i++) { mbar_init(EFULL + 8 * i, 4); mbar_init(EEMPTY + 8 * i, 1); }
        for (int i = 0; i < 4; i++) { mbar_init(IFULL + 8 * i, 1); mbar_init(IEMPTY + 8 * i, 11); }
        mbar_init(VEC, 1); mbar_init(GBAR, 1); mbar_init(LNDONE, 8); mbar_init(LNFREE, 1);
        asm volatile("fence.mbarrier_init.release.cluster;" ::: "memory");
    }
    __syncthreads();
    if (warp >= 12) {
        asm volatile("setmaxnreg.dec.sync.aligned.u32 72;");
        const uint64_t ef = policy_stream();
        if (warp == 15) {
            for (int n = 0; !mbar_test(MODE, 0); n++) { __nanosleep(500); if (n > (1 << 20)) __trap(); }
#pragma unroll 1
            for (int n = 0;; n++) {
                const bool end = lds_acq(POST + 64);
                const uint32_t u = lds_acq(POST + (lane & 15) * 4);
                if (__any_sync(0xffffffffu, u)) {
                    if (u && lane < 16) { sts32(POST + lane * 4, 0); flag_add(&g_flags.at[((u - 1) >> 6) * 32 + ((u - 1) & 31)]); APROF(u - 1); }
                    __syncwarp();
                    n = 0;
                } else if (end) break;
                else { __nanosleep(50); if (n > (1 << 23)) __trap(); }
            }
        } else {
        mbar_wait(GO, 0);
        bool vec = false;
#pragma unroll 1
        for (;;) {
            const int t = __reduce_max_sync(0xffffffffu, claim(&g_flags.bnext));
            if (t < 40) {
                flag_wait_idle(&g_flags.v[0], 2);
                float a0 = 0, a1 = 0;
                const uint32_t* src = (const uint32_t*)(wmod + 2 * DM + t * 64) + lane;
#pragma unroll 1
                for (int k0 = 0; k0 < DM; k0 += 64) {
                    const uint32_t cv = silu2(__ldg((const uint32_t*)cin + k0 / 2 + lane));
#pragma unroll 1
                    for (int k1 = 0; k1 < 64; k1 += 32) {
                        uint32_t wv[32];
#pragma unroll
                        for (int k = 0; k < 32; k++) wv[k] = __ldcs(src + (size_t)(k0 + k1 + k) * (3 * DM));
#pragma unroll
                        for (int k = 0; k < 32; k += 2) {
                            const uint32_t c2 = __shfl_sync(0xffffffffu, cv, (k1 + k) >> 1);
                            a0 += lo_f(c2) * lo_f(wv[k]) + hi_f(c2) * lo_f(wv[k + 1]); a1 += lo_f(c2) * hi_f(wv[k]) + hi_f(c2) * hi_f(wv[k + 1]);
                        }
                    }
                }
                ((uint32_t*)(g_mod + 2 * DM + t * 64))[lane] = pack2(a0, a1);
                __syncwarp();
                if (lane == 0) flag_add(&g_flags.mod);
                continue;
            }
            if (!vec) {
                vec = true;
                if (warp == 12) {
                    flag_wait_idle(&g_flags.mod, 40);
                    if (elect()) { mbar_expect(VEC, 6400); bulk_g2s(sm + SD_VEC, g_mod + 2 * DM, 5120, VEC); bulk_g2s(sm + SD_VEC + 5120, wr, 1280, VEC); }
                    __syncwarp();
                    mbar_wait(VEC, 0);
                }
            }
            const int pos = t - 40, b = pos >> 7;
            if (pos >= sd.bgrows) break;
            const int ls = sd.lsplit[b], row = pos_row(pos);
            flag_wait_idle(&g_flags.o[(pos >> 6) * 32], 4u << ls);
            float av[20];
#pragma unroll
            for (int n = 0; n < 20; n++) av[n] = 0.f;
            const bf16* sl = g_slab + ((size_t)sd.slab[b] * 128 + (pos & 127)) * DM + lane * 4;
#pragma unroll 1
            for (int k = 0; k < (1 << ls); k += 2) {
                uint2 z[2][5];
#pragma unroll
                for (int n = 0; n < 10; n++) z[n / 5][n % 5] = ld_ef(sl + (size_t)(k + n / 5) * (128 * DM) + n % 5 * 128, ef);
#pragma unroll
                for (int n = 0; n < 10; n++) { const uint2 v = z[n / 5][n % 5]; float* a = av + 4 * (n % 5); a[0] += lo_f(v.x); a[1] += hi_f(v.x); a[2] += lo_f(v.y); a[3] += hi_f(v.y); }
            }
            uint2 xn[5];
#pragma unroll
            for (int q2 = 0; q2 < 5; q2++) xn[q2] = ld_ef(x + row * DM + lane * 4 + q2 * 128, ef);
            uint32_t ap[5][2];
#pragma unroll
            for (int n = 0; n < 10; n++) ap[n >> 1][n & 1] = pack2(av[2 * n], av[2 * n + 1]);
            mbar_wait(VEC, 0);
            ln2_row(ap, xn, row, sm + SD_VEC + lane * 8, out, ef, lane);
            __syncwarp();
            if (lane == 0) flag_add(&g_flags.ln[b * 32]);
        }
        }
    } else if (warp >= 8) {
      asm volatile("setmaxnreg.dec.sync.aligned.u32 40;");
      const uint64_t ef = policy_stream();
      bool att = false;
      auto manage = [&]() {
          bar_sync(2, 384);
          attn_manager(mp, sm + (warp - 8) * REC, sm + SD_EPI + (warp - 8) * 12288, ATT + (warp - 8) * 64, POST + (warp - 8) * 16, x, ef);
          bar_sync(2, 384);
      };
      if (warp == 8) {
        uint32_t nxt = claim(&g_flags.next);
        int st = 0, ph = 1, run = 0;
        auto take = [&](int n, int bytes) {
            mbar_wait(EMPTY + 8 * (st + n - 1), ph);
            asm volatile("{ .reg .pred p; setp.lt.u32 p, %2, %3; @p mbarrier.arrive.expect_tx.shared::cta.b64 _, [%0], %1; }"
                :: "r"(FULL + 8 * (st + lane)), "r"(lane ? 0 : bytes), "r"(lane), "r"(n) : "memory");
        };
        auto step = [&](int n) { st += n; if (st == SD_NSL) { st = 0; ph ^= 1; } };
#pragma unroll 1
        for (int q = 0;; q++) {
            const int tk = __reduce_max_sync(0xffffffffu, nxt);
            while (tk >= sd.end[run]) run++;
            const int kind = sd.kind[run], b = sd.block[run], i = tk - (run ? sd.end[run - 1] : 0), ls = sd.lsplit[b];
            mbar_wait(IEMPTY + 8 * (q & 3), ((q >> 2) & 1) ^ 1);
            if (elect()) {
                sts32(IQ + 4 * (q & 3), kind << 12 | b << 8 | (i & 255));
                mbar_arrive(IFULL + 8 * (q & 3));
            }
            __syncwarp();
            const int pad = kind == 2 || kind > 4 ? st & 1 : (12 - st) % 3;
            if (pad) { take(pad, 0); step(pad); }
            int kb0 = 0;
            if (q == 0) {
                if (kind == 0) {
#pragma unroll 1
                    for (; kb0 < 4; kb0++) { take(3, 40960); if (elect()) tma3d(sm + st * SD_SL + 16384, &mp.wv, kb0 * 64, i * 3, FULL + 8 * st); step(3); }
                }
                flag_wait_warp(&g_flags.h, 96);
                if (elect()) mbar_arrive(GO);
#pragma unroll 1
                for (int kb = 0; kb < kb0; kb++) if (elect()) tma2d(sm + kb * 3 * SD_SL, &mp.h, kb * 64, b * 128, FULL + 24 * kb);
            }
            if (kind == 0) {
#pragma unroll 1
                for (int kb = kb0; kb < 10; kb++) {
                    take(3, 40960);
                    if (elect()) { tma2d(sm + st * SD_SL, &mp.h, kb * 64, b * 128, FULL + 8 * st); tma3d(sm + st * SD_SL + 16384, &mp.wv, kb * 64, i * 3, FULL + 8 * st); }
                    if (kb == 8) nxt = claim(&g_flags.next);
                    step(3);
                }
            } else if (kind == 1) {
                if (!att) {
                    if (elect()) mbar_arrive(MODE);
                    manage();
                    if (elect()) asm volatile("st.release.cta.shared.u32 [%0], 1;" :: "r"(POST + 64) : "memory");
                }
                att = true;
                nxt = claim(&g_flags.next);
            } else if (kind == 2 || kind > 4) {
                const int nst = 192 >> ls, kf = (i >> 1) * nst * 32, row = b * 128 + (kind == 6 ? 64 : 0), bytes = kind == 2 ? 28672 : 24576;
                const CUtensorMap* om = kind == 2 ? &mp.o : &mp.o64;
                const uint32_t* af = &g_flags.at[(2 * b + (kind == 2 ? lane >> 4 : kind - 5)) * 32 + (i >> 1) * (32 >> ls) + (lane & ((32 >> ls) - 1))];
                int kb = 0;
                if (!__all_sync(0xffffffffu, ld_rlx(af) >= 2)) {
#pragma unroll 1
                    for (; kb < 6; kb++) { take(2, bytes); if (elect()) tma3d(sm + st * SD_SL + 8192, &mp.wo, kf + kb * 32, (i & 1) * 5, FULL + 8 * st); step(2); }
                    flag_wait_warp(af, 2);
#pragma unroll 1
                    for (int n = 0; n < 6; n++) { const int sl = (st + 2 * n) % SD_NSL; if (elect()) tma2d(sm + sl * SD_SL, om, kf + n * 32, row, FULL + 8 * sl); }
                    if (nst == 6) nxt = claim(&g_flags.next);
                }
#pragma unroll 1
                for (; kb < nst; kb++) {
                    take(2, bytes);
                    if (elect()) { tma3d(sm + st * SD_SL + 8192, &mp.wo, kf + kb * 32, (i & 1) * 5, FULL + 8 * st); tma2d(sm + st * SD_SL, om, kf + kb * 32, row, FULL + 8 * st); }
                    if (kb == nst - 2) nxt = claim(&g_flags.next);
                    step(2);
                }
            } else if (kind == 3) {
                take(3, 40960);
                flag_wait_warp(&g_flags.o[(2 * b + (i >> (ls + 1))) * 32], 4u << ls);
                if (elect())
                    asm volatile("cp.async.bulk.tensor.4d.shared::cluster.global.mbarrier::complete_tx::bytes.L2::cache_hint [%0], [%1, {0, 0, %3, %4}], [%2], %5;"
                        :: "r"(sm + st * SD_SL), "l"((uint64_t)&mp.ln[ls - 3]), "r"(FULL + 8 * st), "r"(i * (32 >> ls)), "r"((int)sd.slab[b]), "l"(ef) : "memory");
                step(3);
                mbar_wait(IEMPTY + 8 * (q & 3), (q >> 2) & 1);
                nxt = claim(&g_flags.next);
            } else {
                if (blockIdx.x < 96) {
                    take(3, 40960);
                    if (elect()) {
#pragma unroll 1
                        for (int c = 0; c < 5; c++) { tma2d(sm + st * SD_SL + c * 4096, &mp.wgate, blockIdx.x * 16, c * 128, FULL + 8 * st); tma2d(sm + st * SD_SL + 20480 + c * 4096, &mp.wup, blockIdx.x * 16, c * 128, FULL + 8 * st); }
                    }
                    step(3);
                }
                if (blockIdx.x < 80) {
                    take(3, 24576);
                    if (elect()) {
#pragma unroll 1
                        for (int c = 0; c < 6; c++) tma2d(sm + st * SD_SL + c * 4096, &mp.wdown, blockIdx.x * 8, c * 256, FULL + 8 * st);
                    }
                }
                if (elect()) {
                    if (!att) { sts32(POST + 64, 1); mbar_arrive(MODE); }
                    flags_release();
                }
                break;
            }
        }
      } else {
        const int wg = warp - 9; int ph = 0;
#pragma unroll 1
        for (int q = 0;; q++) {
            mbar_wait(IFULL + 8 * (q & 3), (q >> 2) & 1);
            const int it = __shfl_sync(0xffffffffu, lds32(IQ + 4 * (q & 3)), 0);
            if (elect()) mbar_arrive(IEMPTY + 8 * (q & 3));
            const int kind = (it >> 12) & 7, b = (it >> 8) & 15, i = it & 255;
            if (kind == 4) break;
            if (kind == 1) { if (!att) manage(); att = true; continue; }
            if ((wg == 2) != (kind == 3)) continue;
            if (kind == 3) {
                mbar_wait(LNDONE, ph); ph ^= 1;
                if (elect()) { mbar_arrive(LNFREE); flag_add(&g_flags.ln[b * 32], 32 >> sd.lsplit[b]); }
            } else {
#pragma unroll 1
                for (int rd = 0; rd < (kind == 2 ? 2 : 1); rd++) {
                    mbar_wait(EFULL + 8 * wg, ph); ph ^= 1;
                    const uint32_t src = sm + SD_EPI + wg * 24576;
                    if (elect()) {
                        const int part = kind == 2 ? rd : wg, half = kind == 2 ? wg : kind - 5;
                        if (kind) tma3d_store(part ? &mp.slab2 : &mp.slab3, (sd.slab[b] + (i >> 1)) * 128 + half * 64, (i & 1) * 5 + part * 3, src, ef, false);
                        else {
                            uint8_t* dst = g_rec + (size_t)((b * 4 + wg * 2) * NH + i) * REC;
                            bulk_s2g_ef(dst, src, 12288, ef); bulk_s2g_ef(dst + NH * REC, src + 12288, 12288, ef);
                        }
                        BULK_COMMIT();
                        BULK_WAIT_READ();
                        mbar_arrive(EEMPTY + 8 * wg);
                    }
                    __syncwarp();
                }
                if (elect()) { BULK_WAIT(); flag_add(kind == 0 ? &g_flags.v[b * 32 + i] : &g_flags.o[(2 * b + (kind == 2 ? wg : kind - 5)) * 32], kind == 2 ? 2 : 1); }
            }
            __syncwarp();
        }
      }
    } else {
        asm volatile("setmaxnreg.inc.sync.aligned.u32 200;");
        const uint64_t ef = policy_stream();
        const int wg = warp >> 2, w = warp & 3;
        int st = 0, ph = 0, eph = 1, lph = 1;
        bool att = false;
        const uint32_t eb = sm + SD_EPI + wg * 24576;
        for (int q = 0;; q++) {
            mbar_wait(IFULL + 8 * (q & 3), (q >> 2) & 1);
            const int itc = __shfl_sync(0xffffffffu, lds32(IQ + 4 * (q & 3)), 0);
            if (lane == 0) mbar_arrive(IEMPTY + 8 * (q & 3));
            const int kind = (itc >> 12) & 7, b = (itc >> 8) & 15, i = itc & 255;
            const int ns = kind == 2 || kind > 4 ? 2 : 3, pad = ns == 2 ? st & 1 : (12 - st) % 3;
            if (pad) {
                mbar_wait(FULL + 8 * st, ph);
                if (lane < pad) mbar_arrive(EMPTY + 8 * (st + lane));
                st += pad; if (st == SD_NSL) { st = 0; ph ^= 1; }
            }
            const uint32_t rel = EMPTY + 8 * lane;
            if (kind == 0) {
                float acc[96];
#pragma unroll
                for (int n = 0; n < 96; n++) acc[n] = 0.f;
                int prev = -1;
                for (int kb = 0; kb < 10; kb++) {
                    FWAIT(FULL + 8 * st, ph);
                    const uint32_t base = sm + st * SD_SL;
                    WG_FENCE();
#pragma unroll
                    for (int ks = 0; ks < 4; ks++)
                        wgmma_ss_n192_tb(acc, mkdesc(base + wg * 8192 + ks * 32, 16, 1024), mkdesc(base + 16384 + ks * 2048, 8192, 1024), (kb | ks) != 0);
                    WG_COMMIT();
                    if (prev >= 0) { WG_WAIT(1); if (lane < ns) mbar_arrive(rel + 8 * prev); }
                    prev = st;
                    st += ns; if (st == SD_NSL) { st = 0; ph ^= 1; }
                }
                WG_WAIT(0);
                if (lane < ns) mbar_arrive(rel + 8 * prev);
                EPROF();
                tile_out<12, true>(acc, eb, EFULL + 8 * wg, EEMPTY + 8 * wg, eph, w, lane);
            } else if (kind == 1) {
                if (!att) {
                    bar_sync(2, 384);
                    attn_units(sm + (warp >> 1) * REC, sm + SD_EPI + (warp >> 1) * 12288 + (warp & 1) * 2048, ATT + (warp >> 1) * 64, warp & 1, lane);
                    bar_sync(2, 384);
                }
                att = true;
            } else if (kind == 2) {
                float acc[96], acc2[64];
#pragma unroll
                for (int n = 0; n < 96; n++) acc[n] = 0.f;
#pragma unroll
                for (int n = 0; n < 64; n++) acc2[n] = 0.f;
                int prev = -1;
                for (int kb = 192 >> sd.lsplit[b]; kb > 0; kb--) {
                    const uint32_t base = sm + st * SD_SL;
                    FWAIT(FULL + 8 * st, ph);
                    WG_FENCE();
#pragma unroll
                    for (int ks = 0; ks < 2; ks++) {
                        const uint64_t da = (mkdesc(base + wg * 4096 + ks * 32, 16, 512) & ~(3ull << 62)) | (2ull << 62);
                        wgmma_ss_n192_tb(acc, da, mkdesc(base + 8192 + ks * 2048, 4096, 1024), 1);
                        wgmma_ss_n128_tb(acc2, da, mkdesc(base + 8192 + 3 * 4096 + ks * 2048, 4096, 1024), 1);
                    }
                    WG_COMMIT();
                    if (prev >= 0) { WG_WAIT(1); if (lane < ns) mbar_arrive(rel + 8 * prev); }
                    prev = st;
                    st += ns; if (st == SD_NSL) { st = 0; ph ^= 1; }
                }
                WG_WAIT(0);
                if (lane < ns) mbar_arrive(rel + 8 * prev);
                EPROF();
                tile_out<12, false>(acc, eb, EFULL + 8 * wg, EEMPTY + 8 * wg, eph, w, lane);
                tile_out<8, false>(acc2, eb, EFULL + 8 * wg, EEMPTY + 8 * wg, eph, w, lane);
            } else if (kind > 4) {
                auto half = [&](auto& acc, auto mma) {
                    int prev = -1;
                    for (int kb = 192 >> sd.lsplit[b]; kb > 0; kb--) {
                        const uint32_t base = sm + st * SD_SL;
                        FWAIT(FULL + 8 * st, ph);
                        WG_FENCE();
#pragma unroll
                        for (int ks = 0; ks < 2; ks++) mma(acc, (mkdesc(base + ks * 32, 16, 512) & ~(3ull << 62)) | (2ull << 62), mkdesc(base + 8192 + wg * 12288 + ks * 2048, 4096, 1024));
                        WG_COMMIT();
                        if (prev >= 0) { WG_WAIT(1); if (lane < 2) mbar_arrive(rel + 8 * prev); }
                        prev = st;
                        st += 2; if (st == SD_NSL) { st = 0; ph ^= 1; }
                    }
                    WG_WAIT(0);
                    if (lane < 2) mbar_arrive(rel + 8 * prev);
                    EPROF();
                };
                if (wg == 0) {
                    float acc[96];
#pragma unroll
                    for (int n = 0; n < 96; n++) acc[n] = 0.f;
                    half(acc, [](float (&d)[96], uint64_t a, uint64_t bd) { wgmma_ss_n192_tb(d, a, bd, 1); });
                    tile_out<12, false>(acc, eb, EFULL, EEMPTY, eph, w, lane);
                } else {
                    float acc[64];
#pragma unroll
                    for (int n = 0; n < 64; n++) acc[n] = 0.f;
                    half(acc, [](float (&d)[64], uint64_t a, uint64_t bd) { wgmma_ss_n128_tb(d, a, bd, 1); });
                    tile_out<8, false>(acc, eb, EFULL + 8, EEMPTY + 8, eph, w, lane);
                }
            } else if (kind == 3) {
                const int ls = sd.lsplit[b], rs = 5 - ls, row = pos_row(b * 128 + (i << rs) + (warp & ((1 << rs) - 1)));
                uint2 xn[5];
#pragma unroll
                for (int q2 = 0; q2 < 5; q2++) xn[q2] = ld_ef(x + row * DM + lane * 4 + q2 * 128, ef);
                mbar_wait(VEC, 0);
                FWAIT(FULL + 8 * st, ph);
                const uint32_t base = sm + st * SD_SL;
#pragma unroll 1
                for (int c = tid; c < (320 << rs); c += 256) {
                    float a0 = 0, a1 = 0;
#pragma unroll 1
                    for (int k = 0; k < (1 << ls); k += 8) {
                        uint32_t z[8];
#pragma unroll
                        for (int u = 0; u < 8; u++) z[u] = lds32(base + c * 4 + ((k + u) * 1280 << rs));
#pragma unroll
                        for (int u = 0; u < 8; u++) { a0 += lo_f(z[u]); a1 += hi_f(z[u]); }
                    }
                    sts32(base + c * 4, pack2(a0, a1));
                }
                bar_sync(1, 256);
                uint32_t av[5][2];
#pragma unroll
                for (int q2 = 0; q2 < 5; q2++) lds64(av[q2], base + (warp & ((1 << rs) - 1)) * 1280 + lane * 8 + q2 * 256);
                PROXY_FENCE();
                __syncwarp();
                if (lane < 3) mbar_arrive(rel + 8 * st);
                st += 3; if (st == SD_NSL) { st = 0; ph ^= 1; }
                if (warp < (1 << rs)) ln2_row(av, xn, row, sm + SD_VEC + lane * 8, out, ef, lane);
                __syncwarp();
                mbar_wait(LNFREE, lph); lph ^= 1;
                if (lane == 0) mbar_arrive(LNDONE);
            } else {
                if (blockIdx.x < 96) {
                    mbar_wait(EEMPTY + 8 * wg, eph);
                    int s1 = st + 3, p1 = ph; if (s1 == SD_NSL) { s1 = 0; p1 ^= 1; }
                    side_tail(sm + st * SD_SL, FULL + 8 * st, ph, sm + s1 * SD_SL, FULL + 8 * s1, p1, sm + SD_EPI, GBAR, out, tid);
                }
                break;
            }
        }
    }
    __syncwarp();
    asm volatile("griddepcontrol.wait;" ::: "memory");
}

typedef CUresult (*EncodeFn)(CUtensorMap*, CUtensorMapDataType, cuuint32_t, void*, const cuuint64_t*, const cuuint64_t*, const cuuint32_t*, const cuuint32_t*,
                             CUtensorMapInterleave, CUtensorMapSwizzle, CUtensorMapL2promotion, CUtensorMapFloatOOBfill);
static EncodeFn s_encode = nullptr;
static void make_map(CUtensorMap* m, const void* p, int rows, int cols, int box_rows, int box_cols = 64) {
    cuuint64_t dims[2] = {(cuuint64_t)cols, (cuuint64_t)rows}, strides[1] = {(cuuint64_t)cols * 2};
    cuuint32_t box[2] = {(cuuint32_t)box_cols, (cuuint32_t)box_rows}, es[2] = {1, 1};
    s_encode(m, CU_TENSOR_MAP_DATA_TYPE_BFLOAT16, 2, (void*)p, dims, strides, box, es, CU_TENSOR_MAP_INTERLEAVE_NONE,
             box_cols == 64 ? CU_TENSOR_MAP_SWIZZLE_128B : box_cols == 32 ? CU_TENSOR_MAP_SWIZZLE_64B : CU_TENSOR_MAP_SWIZZLE_NONE, CU_TENSOR_MAP_L2_PROMOTION_L2_256B, CU_TENSOR_MAP_FLOAT_OOB_FILL_NONE);
}
static void make_map3(CUtensorMap* m, const void* p, int rows, int cols, int box_rows, int box_chunks, int cw = 64) {
    cuuint64_t dims[3] = {(cuuint64_t)cw, (cuuint64_t)rows, (cuuint64_t)cols / cw}, strides[2] = {(cuuint64_t)cols * 2, (cuuint64_t)cw * 2};
    cuuint32_t box[3] = {(cuuint32_t)cw, (cuuint32_t)box_rows, (cuuint32_t)box_chunks}, es[3] = {1, 1, 1};
    s_encode(m, CU_TENSOR_MAP_DATA_TYPE_BFLOAT16, 3, (void*)p, dims, strides, box, es, CU_TENSOR_MAP_INTERLEAVE_NONE,
             cw == 64 ? CU_TENSOR_MAP_SWIZZLE_128B : CU_TENSOR_MAP_SWIZZLE_64B, CU_TENSOR_MAP_L2_PROMOTION_L2_256B, CU_TENSOR_MAP_FLOAT_OOB_FILL_NONE);
}
template <typename T> static void* sym(T& s) { void* p = nullptr; cudaGetSymbolAddress(&p, s); return p; }

static void make_map_ln(CUtensorMap* m, const void* p, int ls) {
    cuuint64_t dims[4] = {128, 5, 128, NSLAB}, strides[3] = {256, DM * 2, 128 * DM * 2};
    cuuint32_t box[4] = {128, 5, (cuuint32_t)(32 >> ls), (cuuint32_t)(1 << ls)}, es[4] = {1, 1, 1, 1};
    s_encode(m, CU_TENSOR_MAP_DATA_TYPE_BFLOAT16, 4, (void*)p, dims, strides, box, es, CU_TENSOR_MAP_INTERLEAVE_NONE,
             CU_TENSOR_MAP_SWIZZLE_NONE, CU_TENSOR_MAP_L2_PROMOTION_L2_256B, CU_TENSOR_MAP_FLOAT_OOB_FILL_NONE);
}
static void make_sched(Sched* sd, const char* order, const char* lsplit) {
    int slab = 0, end = 0, r = 0;
    for (int b = 0; b < 16; b++) { sd->lsplit[b] = lsplit[b] - '0'; sd->slab[b] = slab; slab += 1 << sd->lsplit[b]; }
    sd->bgrows = S_TOK;
    for (; r < NRUN && order[2 * r]; r++) {
        const char k = order[2 * r], c = order[2 * r + 1]; const int b = c <= '9' ? c - '0' : c - 'a' + 10;
        sd->kind[r] = k == 'V' ? 0 : k == 'T' ? 1 : k == 'O' ? 2 : k == 'G' ? 5 : k == 'H' ? 6 : 3; sd->block[r] = b;
        end += k == 'O' || k == 'G' || k == 'H' ? 2 << sd->lsplit[b] : k == 'L' ? 4 << sd->lsplit[b] : k == 'T' ? b : 32;
        sd->end[r] = end;
        if (k == 'L') sd->bgrows -= 128;
    }
    for (; r <= NRUN; r++) { sd->end[r] = 65535; sd->kind[r] = 4; sd->block[r] = 0; }
}

extern "C" void kernel_launch(void* const* d_in, const int* in_sizes, int n_in, void* d_out, int out_size) {
    const bf16 *x = (const bf16*)d_in[0], *mem0 = (const bf16*)d_in[1], *Wq = (const bf16*)d_in[2], *Wk = (const bf16*)d_in[3],
               *Wv = (const bf16*)d_in[4], *Wo = (const bf16*)d_in[5], *wr = (const bf16*)d_in[8], *wgate = (const bf16*)d_in[9],
               *wup = (const bf16*)d_in[10], *wdown = (const bf16*)d_in[11], *c = (const bf16*)d_in[12], *wmod = (const bf16*)d_in[13];
    bf16* out = (bf16*)d_out;
    if (!s_encode) {
        cudaDriverEntryPointQueryResult qr;
        cudaGetDriverEntryPoint("cuTensorMapEncodeTiled", (void**)&s_encode, cudaEnableDefault, &qr);
        cudaFuncSetAttribute(k_side, cudaFuncAttributeMaxDynamicSharedMemorySize, SD_SMEM);
        cudaFuncSetAttribute(k_chain, cudaFuncAttributeMaxDynamicSharedMemorySize, C_SMEM);
    }
    ChainMaps cm; SideMaps sd; Sched sc;
    make_map(&sd.h, sym(g_h), S_TOK, DM, 128); make_map3(&sd.wv, Wv, DM, HD, 64, 3);
    make_map3(&sd.ost, sym(g_o), S_TOK, HD, 32, 3); make_map(&sd.o, sym(g_o), S_TOK, HD, 128, 32); make_map(&sd.o64, sym(g_o), S_TOK, HD, 64, 32); make_map3(&sd.wo, Wo, HD, DM, 32, 5);
    make_map3(&sd.slab3, sym(g_slab), NSLAB * 128, DM, 64, 3); make_map3(&sd.slab2, sym(g_slab), NSLAB * 128, DM, 64, 2);
    for (int i = 0; i < 3; i++) make_map_ln(&sd.ln[i], sym(g_slab), i + 3);
    make_map(&sd.wgate, wgate, DM, FF, 128, 16); make_map(&sd.wup, wup, DM, FF, 128, 16); make_map(&sd.wdown, wdown, FF, DM, 256, 8);
    make_map(&cm.wq, Wq, DM, HD, 128); make_map(&cm.wk, Wk, DM, HD, 128); make_map(&cm.wv, Wv, DM, HD, 128); make_map3(&cm.wo, Wo, HD, DM, 32, 7, 32);
    make_map3(&cm.h1, sym(g_h), S_TOK, DM, 32, 1); make_map3(&cm.h4, sym(g_h), S_TOK, DM, 32, 4);
    make_map(&cm.wmod, wmod, DM, 6 * DM, 160, 16);
    ChainArgs ar = {x, mem0, c, 700, 100, 0, {1, 4, 3, 0}};
    const char *order = "V0V1V2V3T7V4V5V6O0V7O1V8O2V9O3VaO4VbO5VcO6VdO7VeO8VfO9OaT2ObOcOdGeHeGfHfLdLeLf",
               *lsplit = "1111111112233434";
    make_sched(&sc, order, lsplit);
    k_chain<<<96, 384, C_SMEM>>>(cm, ar);
    cudaLaunchConfig_t cfg = {};
    cfg.gridDim = dim3(N_SIDE); cfg.blockDim = dim3(512); cfg.dynamicSmemBytes = SD_SMEM; cfg.stream = cudaStreamPerThread;
    cudaLaunchAttribute at[1]; at[0].id = cudaLaunchAttributeProgrammaticStreamSerialization; at[0].val.programmaticStreamSerializationAllowed = 1;
    cfg.attrs = at; cfg.numAttrs = 1;
    cudaLaunchKernelEx(&cfg, k_side, sd, sc, x, wr, c, wmod, out);
}
```
